```python
import torch

def _softmax(x, axis=-1):
    return torch.softmax(x, dim=axis)
def _gelu(x):
    return torch.nn.functional.gelu(x, approximate="tanh")
def _silu(x):
    return torch.nn.functional.silu(x)
def _sigmoid(x):
    return torch.sigmoid(x)
def _layernorm(x, axis=-1, eps=1e-5):
    m = x.mean(dim=axis, keepdim=True)
    v = x.var(dim=axis, keepdim=True, unbiased=False)
    return (x - m) / torch.sqrt(v + eps)
def _scatter_add(tgt, idx, src, axis=0):
    return tgt.clone().index_add_(axis, idx, src)
def _segment_sum(src, seg, n):
    out = torch.zeros((n,) + src.shape[1:], dtype=src.dtype)
    return out.index_add_(0, seg, src)
def _pad(x, pw):
    flat = tuple(v for pair in reversed(pw) for v in pair)
    return torch.nn.functional.pad(x, flat)

kernel_name = 'sequential_preLN__ssm_conv_s4__glu_gated_reglu__prompt'

def setup_inputs():

    _w = (lambda a: (lambda t: t.to(torch.bfloat16) if t.is_floating_point() else t)(torch.as_tensor(a)))
    def _A_setup():
        B, L, D, N = 1, 2048, 576, 128
        A_re = -(lambda _x: torch.exp(torch.as_tensor(_x)))((lambda *s: torch.randn(*s, dtype=torch.bfloat16) * 6.4)(D, N))
        A_im = torch.pi * (lambda *s: torch.randn(*s, dtype=torch.bfloat16) * 0.05)(D, N)
        B_re = (lambda *s: torch.randn(*s, dtype=torch.bfloat16) * 0.05)(D, N)
        B_im = (lambda *s: torch.randn(*s, dtype=torch.bfloat16) * 0.05)(D, N)
        C_re = (lambda *s: torch.randn(*s, dtype=torch.bfloat16) * 0.05)(D, N)
        C_im = (lambda *s: torch.randn(*s, dtype=torch.bfloat16) * 0.05)(D, N)
        log_dt = (lambda *s: torch.randn(*s, dtype=torch.bfloat16) * 0.05)(D) * 0.5 - 4.0
        Dskip = (lambda *s: torch.randn(*s, dtype=torch.bfloat16) * 0.05)(D)
        return {
            "u": _w((lambda *s: torch.randn(*s, dtype=torch.bfloat16) * 0.05)(B, L, D)),
            "A_re": _w(A_re),
            "A_im": _w(A_im),
            "B_re": _w(B_re),
            "B_im": _w(B_im),
            "C_re": _w(C_re),
            "C_im": _w(C_im),
            "log_dt": _w(log_dt),
            "Dskip": _w(Dskip),
        }
    _A_in = _A_setup()

    def _B_setup():
        B, S, D, F = 1, 2048, 576, 4608
        return {
            "x": _w((lambda *s: torch.randn(*s, dtype=torch.bfloat16) * 0.05)(B, S, D)),
            "W_gate": _w((lambda *s: torch.randn(*s, dtype=torch.bfloat16) * 0.4)(D, F) * (2.0 / D) ** 0.5),
            "W_up": _w((lambda *s: torch.randn(*s, dtype=torch.bfloat16) * 0.4)(D, F) * (2.0 / D) ** 0.5),
            "W_down": _w((lambda *s: torch.randn(*s, dtype=torch.bfloat16) * 0.4)(F, D) * (1.0 / F) ** 0.5),
        }
    _B_in = _B_setup()

    return {
        "A_u": _A_in["u"],
        "A_A_re": _A_in["A_re"],
        "A_A_im": _A_in["A_im"],
        "A_B_re": _A_in["B_re"],
        "A_B_im": _A_in["B_im"],
        "A_C_re": _A_in["C_re"],
        "A_C_im": _A_in["C_im"],
        "A_log_dt": _A_in["log_dt"],
        "A_Dskip": _A_in["Dskip"],
        "B_x": _B_in["x"],
        "B_W_gate": _B_in["W_gate"],
        "B_W_up": _B_in["W_up"],
        "B_W_down": _B_in["W_down"],
    }

def reference(A_u, A_A_re, A_A_im, A_B_re, A_B_im, A_C_re, A_C_im, A_log_dt, A_Dskip, B_x, B_W_gate, B_W_up, B_W_down):
    def _A_ref(u, A_re, A_im, B_re, B_im, C_re, C_im, log_dt, Dskip):
        Bsz, L, D = u.shape
        dt = torch.exp(log_dt)[:, None]
        A = A_re + 1j * A_im
        Bc = B_re + 1j * B_im
        Cc = C_re + 1j * C_im
        logdA = dt * A
        dB = dt * Bc
        l = (lambda x, dt: x.to(dt))(torch.arange(L), A_re.dtype)
        P = torch.exp(logdA[:, :, None] * l[None, None, :])
        K = torch.einsum("dn,dnl,dn->dl", Cc, P, dB).real
        L2 = 2 * L
        Kp = _pad(K, ((0, 0), (0, L)))
        up = (lambda x, *d: x.permute(*d))(u, 0, 2, 1)
        up = _pad(up, ((0, 0), (0, 0), (0, L)))
        Kf = (lambda x, axes=(-2,-1): torch.fft.rfft2(x.float(), dim=axes))(Kp[:, None, :], axes=(-2, -1))
        Uf = (lambda x, axes=(-2,-1): torch.fft.rfft2(x.float(), dim=axes))(up[:, :, None, :], axes=(-2, -1))
        Yf = Uf * Kf[None, :, :, :]
        y = (lambda x, s, axes=(-2,-1): torch.fft.irfft2(x, s=s, dim=axes).to(torch.bfloat16))(Yf, (1, L2), axes=(-2, -1))[:, :, 0, :L]
        y = (lambda x, *d: x.permute(*d))(y, 0, 2, 1) + u * Dskip[None, None, :]
        return y

    def _B_ref(x, W_gate, W_up, W_down):
        gate = torch.einsum("bsd,df->bsf", x, W_gate)
        up = torch.einsum("bsd,df->bsf", x, W_up)
        gate = gate * (lambda x, dt: x.to(dt))(gate > 0, gate.dtype)
        h = gate * up
        return torch.einsum("bsf,fd->bsd", h, W_down)

    x = A_u
    h = x + _A_ref(_layernorm(x, axis=-1), A_A_re, A_A_im, A_B_re, A_B_im, A_C_re, A_C_im, A_log_dt, A_Dskip)
    h2 = h + _B_ref(_layernorm(h, axis=-1), B_W_gate, B_W_up, B_W_down)
    return h2
```

```cpp
#include <cuda_runtime.h>
#include <cuda_bf16.h>
#include <cuda.h>
#include <stdint.h>

constexpr int SEQ = 2048, DM = 576, FF = 4608, NST = 128;
#define HP 2048

struct __align__(1024) Scratch {
  unsigned sync[48 * 32];
  unsigned cnt[16 * 9 * 8 + 128];
  unsigned cs[8 * 1024];
  uint2 hbit[DM * 4];
  long long prof[132 * 160 + 128];
  __align__(1024) __nv_bfloat16 U[144 * 128 * 64];
  __nv_bfloat16 X[144 * 128 * 64];
  __nv_bfloat16 hT[DM * HP];
  uint4 part[16 * 9 * 3 * 1024];
};
__device__ Scratch g_scr;
constexpr int C_U = 0, C_EP = 32, C_H = 64, C_CS = 64 + 9 * 32, C_Z = C_CS + 8 * 32, C_R = C_Z + 16 * 32;

#define STAMP(slot)
#define GSTAMP(slot)
#define GST32(slot)
#define PROF_DUMP()
#define PROF_INIT()
__device__ __forceinline__ uint32_t smem_u32(const void* p) { return (uint32_t)__cvta_generic_to_shared(p); }
__device__ __forceinline__ void mbar_init(uint32_t bar, uint32_t cnt) { asm volatile("mbarrier.init.shared::cta.b64 [%0], %1;" :: "r"(bar), "r"(cnt)); }
__device__ __forceinline__ void mbar_arrive(uint32_t bar) { asm volatile("mbarrier.arrive.shared::cta.b64 _, [%0];" :: "r"(bar) : "memory"); }
__device__ __forceinline__ void mbar_arrive_cl(uint32_t bar) { asm volatile("mbarrier.arrive.shared::cluster.b64 _, [%0];" :: "r"(bar) : "memory"); }
__device__ __forceinline__ void mbar_expect_tx(uint32_t bar, uint32_t bytes) { asm volatile("mbarrier.arrive.expect_tx.shared::cta.b64 _, [%0], %1;" :: "r"(bar), "r"(bytes) : "memory"); }
__device__ __forceinline__ bool mbar_try(uint32_t bar, uint32_t parity) {
  uint32_t ok; asm volatile("{\n.reg .pred p;\nmbarrier.try_wait.parity.shared::cta.b64 p, [%1], %2;\nselp.u32 %0, 1, 0, p;\n}" : "=r"(ok) : "r"(bar), "r"(parity) : "memory"); return ok; }
__device__ __forceinline__ void mbar_wait(uint32_t bar, uint32_t parity) {
  #pragma unroll 1
  for (int it = 0; it < (1 << 20); it++) { if (mbar_try(bar, parity)) return; }
  __trap();
}
__device__ __forceinline__ void mbar_wait2(uint32_t b0, uint32_t p0, uint32_t b1, uint32_t p1) {
  #pragma unroll 1
  for (int it = 0; it < (1 << 20); it++) {
    uint32_t ok;
    asm volatile("{\n.reg .pred p, q;\nmbarrier.try_wait.parity.shared::cta.b64 p, [%1], %2;\nmbarrier.try_wait.parity.shared::cta.b64 q, [%3], %4;\n"
                 "and.pred p, p, q;\nselp.u32 %0, 1, 0, p;\n}" : "=r"(ok) : "r"(b0), "r"(p0), "r"(b1), "r"(p1) : "memory");
    if (ok) return;
  }
  __trap();
}
__device__ __forceinline__ void mbar_wait3(uint32_t b0, uint32_t p0, uint32_t b1, uint32_t p1, uint32_t b2, uint32_t p2) {
  #pragma unroll 1
  for (int it = 0; it < (1 << 20); it++) {
    uint32_t ok;
    asm volatile("{\n.reg .pred p, q, r;\nmbarrier.try_wait.parity.shared::cta.b64 p, [%1], %2;\nmbarrier.try_wait.parity.shared::cta.b64 q, [%3], %4;\n"
                 "mbarrier.try_wait.parity.shared::cta.b64 r, [%5], %6;\nand.pred p, p, q;\nand.pred p, p, r;\nselp.u32 %0, 1, 0, p;\n}"
                 : "=r"(ok) : "r"(b0), "r"(p0), "r"(b1), "r"(p1), "r"(b2), "r"(p2) : "memory");
    if (ok) return;
  }
  __trap();
}
__device__ __forceinline__ bool bar_or(int id, uint32_t v) {
  uint32_t r;
  asm volatile("{\n.reg .pred p, q;\nsetp.ne.u32 p, %2, 0;\nbar.red.or.pred q, %1, 128, p;\nselp.u32 %0, 1, 0, q;\n}" : "=r"(r) : "r"(id), "r"(v) : "memory");
  return r;
}
__device__ __forceinline__ bool elect_one() { uint32_t p; asm volatile("{\n.reg .pred P;\nelect.sync _|P, 0xffffffff;\nselp.u32 %0, 1, 0, P;\n}" : "=r"(p)); return p; }
__device__ __forceinline__ void bulk_g2s(uint32_t dst, const void* src, uint32_t bytes, uint32_t bar) {
  asm volatile("cp.async.bulk.shared::cluster.global.mbarrier::complete_tx::bytes [%0], [%1], %2, [%3];" :: "r"(dst), "l"(src), "r"(bytes), "r"(bar) : "memory"); }
__device__ __forceinline__ void bulk_s2g(void* dst, uint32_t src, uint32_t bytes) {
  asm volatile("cp.async.bulk.global.shared::cta.bulk_group [%0], [%1], %2;" :: "l"(dst), "r"(src), "r"(bytes) : "memory"); }
__device__ __forceinline__ void bulk_red_bf16(void* dst, uint32_t src, uint32_t bytes) {
  asm volatile("cp.reduce.async.bulk.global.shared::cta.bulk_group.add.noftz.bf16 [%0], [%1], %2;" :: "l"(dst), "r"(src), "r"(bytes) : "memory"); }
__device__ __forceinline__ void tma2d(uint32_t dst, const CUtensorMap* m, int x, int y, uint32_t bar) {
  asm volatile("cp.async.bulk.tensor.2d.shared::cluster.global.mbarrier::complete_tx::bytes [%0], [%1, {%3, %4}], [%2];" :: "r"(dst), "l"(m), "r"(bar), "r"(x), "r"(y) : "memory"); }
__device__ __forceinline__ void tma2d_mc(uint32_t dst, const CUtensorMap* m, int x, int y, uint32_t bar, uint16_t mask) {
  asm volatile("cp.async.bulk.tensor.2d.shared::cluster.global.mbarrier::complete_tx::bytes.multicast::cluster [%0], [%1, {%3, %4}], [%2], %5;" :: "r"(dst), "l"(m), "r"(bar), "r"(x), "r"(y), "h"(mask) : "memory"); }
__device__ __forceinline__ void tma2d_store(const CUtensorMap* m, int x, int y, uint32_t src) {
  asm volatile("cp.async.bulk.tensor.2d.global.shared::cta.bulk_group [%0, {%2, %3}], [%1];" :: "l"(m), "r"(src), "r"(x), "r"(y) : "memory"); }
__device__ __forceinline__ void tma2d_prefetch(const CUtensorMap* m, int x, int y) {
  asm volatile("cp.async.bulk.prefetch.tensor.2d.L2.global [%0, {%1, %2}];" :: "l"(m), "r"(x), "r"(y) : "memory"); }
__device__ __forceinline__ void bulk_commit() { asm volatile("cp.async.bulk.commit_group;" ::: "memory"); }
__device__ __forceinline__ void bulk_wait_read() { asm volatile("cp.async.bulk.wait_group.read 0;" ::: "memory"); }
__device__ __forceinline__ void bulk_wait_all() { asm volatile("cp.async.bulk.wait_group 0;" ::: "memory"); }
__device__ __forceinline__ void fence_async_smem() { asm volatile("fence.proxy.async.shared::cta;" ::: "memory"); }
__device__ __forceinline__ void fence_async_all() { asm volatile("fence.proxy.async;" ::: "memory"); }
__device__ __forceinline__ void wg_fence() { asm volatile("wgmma.fence.sync.aligned;" ::: "memory"); }
__device__ __forceinline__ void wg_commit() { asm volatile("wgmma.commit_group.sync.aligned;" ::: "memory"); }
template<int N> __device__ __forceinline__ void wg_wait() { asm volatile("wgmma.wait_group.sync.aligned %0;" :: "n"(N) : "memory"); }
__device__ __forceinline__ uint64_t make_desc(uint32_t addr, uint32_t lbo, uint32_t sbo, uint32_t swz) {
  return (uint64_t)((addr & 0x3FFFF) >> 4) | ((uint64_t)(lbo >> 4) << 16) | ((uint64_t)(sbo >> 4) << 32) | ((uint64_t)swz << 62); }
__device__ __forceinline__ void cluster_sync() { asm volatile("barrier.cluster.arrive.aligned;\nbarrier.cluster.wait.aligned;" ::: "memory"); }
__device__ __forceinline__ uint32_t cluster_rank() { uint32_t r; asm volatile("mov.u32 %0, %%cluster_ctarank;" : "=r"(r)); return r; }
__device__ __forceinline__ uint32_t pack_bf16(float lo, float hi) { uint32_t r; asm("cvt.rn.bf16x2.f32 %0, %1, %2;" : "=r"(r) : "f"(hi), "f"(lo)); return r; }
__device__ __forceinline__ uint32_t pack_bf16_relu(float lo, float hi) { uint32_t r; asm("cvt.rn.relu.bf16x2.f32 %0, %1, %2;" : "=r"(r) : "f"(hi), "f"(lo)); return r; }
__device__ __forceinline__ uint32_t mul_bf16x2(uint32_t a, uint32_t b) { uint32_t r; asm("mul.rn.bf16x2 %0, %1, %2;" : "=r"(r) : "r"(a), "r"(b)); return r; }
__device__ __forceinline__ uint32_t neq2(uint32_t a, uint32_t b, uint32_t t) { uint32_t r; asm("lop3.b32 %0, %1, %2, %3, 0x7e;" : "=r"(r) : "r"(a), "r"(b), "r"(t)); return r; }
__device__ __forceinline__ float bf_lo(uint32_t w) { return __uint_as_float(w << 16); }
__device__ __forceinline__ float bf_hi(uint32_t w) { return __uint_as_float(w & 0xffff0000u); }
__device__ __forceinline__ float bf_round(float x) { return bf_hi(pack_bf16(0.f, x)); }
__device__ __forceinline__ float sqrt_fast(float x) { float r; asm("sqrt.approx.ftz.f32 %0, %1;" : "=f"(r) : "f"(x)); return r; }
__device__ __forceinline__ float rcp_fast(float x) { float r; asm("rcp.approx.ftz.f32 %0, %1;" : "=f"(r) : "f"(x)); return r; }
__device__ __forceinline__ float ln_sd(float var) { return bf_round(sqrt_fast(bf_round(bf_round(var) + 1e-5f))); }
__device__ __forceinline__ unsigned ld_relaxed(const unsigned* p) { unsigned v; asm volatile("ld.relaxed.gpu.global.u32 %0, [%1];" : "=r"(v) : "l"(p) : "memory"); return v; }
__device__ __forceinline__ void st_relaxed(unsigned* p, unsigned v) { asm volatile("st.relaxed.gpu.global.u32 [%0], %1;" :: "l"(p), "r"(v) : "memory"); }
__device__ __forceinline__ void ldsm4_t(uint32_t addr, uint32_t& a, uint32_t& b, uint32_t& c, uint32_t& d) {
  asm volatile("ldmatrix.sync.aligned.m8n8.x4.trans.shared.b16 {%0, %1, %2, %3}, [%4];" : "=r"(a), "=r"(b), "=r"(c), "=r"(d) : "r"(addr) : "memory"); }
__device__ __forceinline__ void stsm4(uint32_t addr, uint32_t a, uint32_t b, uint32_t c, uint32_t d) {
  asm volatile("stmatrix.sync.aligned.m8n8.x4.shared.b16 [%0], {%1, %2, %3, %4};" :: "r"(addr), "r"(a), "r"(b), "r"(c), "r"(d) : "memory"); }
__device__ __forceinline__ void sts128(uint32_t addr, uint32_t a, uint32_t b, uint32_t c, uint32_t d) {
  asm volatile("st.shared.v4.b32 [%0], {%1, %2, %3, %4};" :: "r"(addr), "r"(a), "r"(b), "r"(c), "r"(d) : "memory"); }
__device__ __forceinline__ uint4 lds128(uint32_t addr) {
  uint4 v; asm volatile("ld.shared.v4.b32 {%0, %1, %2, %3}, [%4];" : "=r"(v.x), "=r"(v.y), "=r"(v.z), "=r"(v.w) : "r"(addr) : "memory"); return v; }
__device__ __forceinline__ float4 lds128f(uint32_t addr) {
  float4 v; asm volatile("ld.shared.v4.f32 {%0, %1, %2, %3}, [%4];" : "=f"(v.x), "=f"(v.y), "=f"(v.z), "=f"(v.w) : "r"(addr) : "memory"); return v; }
__device__ __forceinline__ unsigned ld_acquire(const unsigned* p) { unsigned v; asm volatile("ld.acquire.gpu.global.u32 %0, [%1];" : "=r"(v) : "l"(p) : "memory"); return v; }
__device__ __forceinline__ void st_release(unsigned* p, unsigned v) { asm volatile("st.release.gpu.global.u32 [%0], %1;" :: "l"(p), "r"(v) : "memory"); }
__device__ __forceinline__ void red_add(unsigned* p, unsigned v) { asm volatile("red.release.gpu.global.add.u32 [%0], %1;" :: "l"(p), "r"(v) : "memory"); }
__device__ __forceinline__ void red_relaxed(unsigned* p) { asm volatile("red.relaxed.gpu.global.add.u32 [%0], 1;" :: "l"(p) : "memory"); }
__device__ __forceinline__ void poll_ge(const unsigned* p, unsigned target) {
  int it = 0;
  while ((int)(ld_relaxed(p) - target) < 0) { if (++it > (1 << 22)) __trap(); }
}
__device__ __forceinline__ void poll_ge_warp(const unsigned* p, unsigned target) {
  int it = 0;
  #pragma unroll 1
  while (!__all_sync(~0u, (int)(ld_relaxed(p) - target) >= 0)) { if (++it > (1 << 22)) __trap(); }
}
__device__ __forceinline__ void ldsm4(uint32_t addr, uint32_t& a, uint32_t& b, uint32_t& c, uint32_t& d) {
  asm volatile("ldmatrix.sync.aligned.m8n8.x4.shared.b16 {%0, %1, %2, %3}, [%4];" : "=r"(a), "=r"(b), "=r"(c), "=r"(d) : "r"(addr) : "memory"); }
__device__ __forceinline__ void stsm4_t(uint32_t addr, uint32_t a, uint32_t b, uint32_t c, uint32_t d) {
  asm volatile("stmatrix.sync.aligned.m8n8.x4.trans.shared.b16 [%0], {%1, %2, %3, %4};" :: "r"(addr), "r"(a), "r"(b), "r"(c), "r"(d) : "memory"); }
__device__ __forceinline__ uint32_t lds32(uint32_t addr) { uint32_t v; asm volatile("ld.shared.b32 %0, [%1];" : "=r"(v) : "r"(addr) : "memory"); return v; }
__device__ __forceinline__ uint2 lds64(uint32_t addr) { uint2 v; asm volatile("ld.shared.v2.b32 {%0, %1}, [%2];" : "=r"(v.x), "=r"(v.y) : "r"(addr) : "memory"); return v; }
__device__ __forceinline__ void sts64(uint32_t addr, uint32_t a, uint32_t b) { asm volatile("st.shared.v2.b32 [%0], {%1, %2};" :: "r"(addr), "r"(a), "r"(b) : "memory"); }
__device__ __forceinline__ uint32_t ldg16(const __nv_bfloat16* p) { return __ldg((const unsigned short*)p); }
__device__ __forceinline__ uint32_t lds16(uint32_t addr) { uint32_t v; asm volatile("ld.shared.u16 %0, [%1];" : "=r"(v) : "r"(addr) : "memory"); return v; }
__device__ __forceinline__ void sts16(uint32_t addr, uint32_t v) { asm volatile("st.shared.u16 [%0], %1;" :: "r"(addr), "r"(v) : "memory"); }
__device__ __forceinline__ void sts32(uint32_t addr, uint32_t v) { asm volatile("st.shared.b32 [%0], %1;" :: "r"(addr), "r"(v) : "memory"); }
__device__ __forceinline__ uint32_t add_bf16x2(uint32_t a, uint32_t b) { uint32_t r; asm("add.rn.bf16x2 %0, %1, %2;" : "=r"(r) : "r"(a), "r"(b)); return r; }
__device__ __forceinline__ uint32_t fma_bf16x2(uint32_t a, uint32_t b, uint32_t c) { uint32_t r; asm("fma.rn.bf16x2 %0, %1, %2, %3;" : "=r"(r) : "r"(a), "r"(b), "r"(c)); return r; }
__device__ __forceinline__ void bar_sync(int id, int n) { asm volatile("bar.sync %0, %1;" :: "r"(id), "r"(n) : "memory"); }
__device__ __forceinline__ void l2_prefetch(const void* p, uint32_t bytes) { asm volatile("cp.async.bulk.prefetch.L2.global [%0], %1;" :: "l"(p), "r"(bytes) : "memory"); }
__device__ __forceinline__ float ldbf(const __nv_bfloat16* p) { return __uint_as_float((uint32_t)__ldg((const unsigned short*)p) << 16); }
template<int R> __device__ __forceinline__ void reg_dec() { asm volatile("setmaxnreg.dec.sync.aligned.u32 %0;" :: "n"(R)); }
template<int R> __device__ __forceinline__ void reg_inc() { asm volatile("setmaxnreg.inc.sync.aligned.u32 %0;" :: "n"(R)); }
template<int N> __device__ __forceinline__ void keepu(uint32_t* d) {
  #pragma unroll
  for (int i = 0; i < N; i++) asm volatile("" : "+r"(d[i]) :: "memory");
}
template<int N> __device__ __forceinline__ void keep(float* d) {
  #pragma unroll
  for (int i = 0; i < N; i++) asm volatile("" : "+f"(d[i]) :: "memory");
}

template<int I> struct IC { static constexpr int v = I; };
template<int B, int E, class Fn> __device__ __forceinline__ void sfor(Fn&& f) { if constexpr (B < E) { f(IC<B>{}); sfor<B + 1, E>(f); } }
constexpr uint32_t SMEM_BASE = 1024;
constexpr uint32_t DESC_HI_128 = (1024 >> 4) | (1u << 30);
__host__ __device__ constexpr uint32_t desc_lo(uint32_t off, uint32_t lbo) { return ((SMEM_BASE + off) >> 4) | ((lbo >> 4) << 16); }

template<int TB, uint32_t BOFF, uint32_t BHI, int SD>
__device__ __forceinline__ void wgmma_rs_8(float* d, uint32_t a0, uint32_t a1, uint32_t a2, uint32_t a3, uint32_t blo) {
  if constexpr (SD) asm volatile("{\n.reg .b32 tb;\n.reg .b64 db;\n"
    "add.u32 tb, %8, %10;\nmov.b64 db, {tb, %11};\n"
    "wgmma.mma_async.sync.aligned.m64n8k16.f32.bf16.bf16 {%0, %1, %2, %3}, {%4, %5, %6, %7}, db, 1, 1, 1, %9;\n}\n"
    : "+f"(d[0]), "+f"(d[1]), "+f"(d[2]), "+f"(d[3])
    : "r"(a0), "r"(a1), "r"(a2), "r"(a3), "r"(blo), "n"(TB), "n"(BOFF), "n"(BHI));
  else asm volatile("{\n.reg .b32 tb;\n.reg .b64 db;\n"
    "add.u32 tb, %8, %10;\nmov.b64 db, {tb, %11};\n"
    "wgmma.mma_async.sync.aligned.m64n8k16.f32.bf16.bf16 {%0, %1, %2, %3}, {%4, %5, %6, %7}, db, 0, 1, 1, %9;\n}\n"
    : "=f"(d[0]), "=f"(d[1]), "=f"(d[2]), "=f"(d[3])
    : "r"(a0), "r"(a1), "r"(a2), "r"(a3), "r"(blo), "n"(TB), "n"(BOFF), "n"(BHI));
}

template<int TB, uint32_t BOFF, uint32_t BHI, int SD>
__device__ __forceinline__ void wgmma_rs_32(float* d, uint32_t a0, uint32_t a1, uint32_t a2, uint32_t a3, uint32_t blo) {
  if constexpr (SD) asm volatile("{\n.reg .b32 tb;\n.reg .b64 db;\n"
    "add.u32 tb, %20, %22;\nmov.b64 db, {tb, %23};\n"
    "wgmma.mma_async.sync.aligned.m64n32k16.f32.bf16.bf16 {%0, %1, %2, %3, %4, %5, %6, %7, %8, %9, %10, %11, %12, %13, %14, %15}, {%16, %17, %18, %19}, db, 1, 1, 1, %21;\n}\n"
    : "+f"(d[0]), "+f"(d[1]), "+f"(d[2]), "+f"(d[3]), "+f"(d[4]), "+f"(d[5]), "+f"(d[6]), "+f"(d[7]), "+f"(d[8]), "+f"(d[9]), "+f"(d[10]), "+f"(d[11]), "+f"(d[12]), "+f"(d[13]), "+f"(d[14]), "+f"(d[15])
    : "r"(a0), "r"(a1), "r"(a2), "r"(a3), "r"(blo), "n"(TB), "n"(BOFF), "n"(BHI));
  else asm volatile("{\n.reg .b32 tb;\n.reg .b64 db;\n"
    "add.u32 tb, %20, %22;\nmov.b64 db, {tb, %23};\n"
    "wgmma.mma_async.sync.aligned.m64n32k16.f32.bf16.bf16 {%0, %1, %2, %3, %4, %5, %6, %7, %8, %9, %10, %11, %12, %13, %14, %15}, {%16, %17, %18, %19}, db, 0, 1, 1, %21;\n}\n"
    : "=f"(d[0]), "=f"(d[1]), "=f"(d[2]), "=f"(d[3]), "=f"(d[4]), "=f"(d[5]), "=f"(d[6]), "=f"(d[7]), "=f"(d[8]), "=f"(d[9]), "=f"(d[10]), "=f"(d[11]), "=f"(d[12]), "=f"(d[13]), "=f"(d[14]), "=f"(d[15])
    : "r"(a0), "r"(a1), "r"(a2), "r"(a3), "r"(blo), "n"(TB), "n"(BOFF), "n"(BHI));
}

template<int TB, uint32_t BOFF, uint32_t BHI, int SD>
__device__ __forceinline__ void wgmma_rs_64(float* d, uint32_t a0, uint32_t a1, uint32_t a2, uint32_t a3, uint32_t blo) {
  if constexpr (SD) asm volatile("{\n.reg .b32 tb;\n.reg .b64 db;\n"
    "add.u32 tb, %36, %38;\nmov.b64 db, {tb, %39};\n"
    "wgmma.mma_async.sync.aligned.m64n64k16.f32.bf16.bf16 {%0, %1, %2, %3, %4, %5, %6, %7, %8, %9, %10, %11, %12, %13, %14, %15, %16, %17, %18, %19, %20, %21, %22, %23, %24, %25, %26, %27, %28, %29, %30, %31}, {%32, %33, %34, %35}, db, 1, 1, 1, %37;\n}\n"
    : "+f"(d[0]), "+f"(d[1]), "+f"(d[2]), "+f"(d[3]), "+f"(d[4]), "+f"(d[5]), "+f"(d[6]), "+f"(d[7]), "+f"(d[8]), "+f"(d[9]), "+f"(d[10]), "+f"(d[11]), "+f"(d[12]), "+f"(d[13]), "+f"(d[14]), "+f"(d[15]), "+f"(d[16]), "+f"(d[17]), "+f"(d[18]), "+f"(d[19]), "+f"(d[20]), "+f"(d[21]), "+f"(d[22]), "+f"(d[23]), "+f"(d[24]), "+f"(d[25]), "+f"(d[26]), "+f"(d[27]), "+f"(d[28]), "+f"(d[29]), "+f"(d[30]), "+f"(d[31])
    : "r"(a0), "r"(a1), "r"(a2), "r"(a3), "r"(blo), "n"(TB), "n"(BOFF), "n"(BHI));
  else asm volatile("{\n.reg .b32 tb;\n.reg .b64 db;\n"
    "add.u32 tb, %36, %38;\nmov.b64 db, {tb, %39};\n"
    "wgmma.mma_async.sync.aligned.m64n64k16.f32.bf16.bf16 {%0, %1, %2, %3, %4, %5, %6, %7, %8, %9, %10, %11, %12, %13, %14, %15, %16, %17, %18, %19, %20, %21, %22, %23, %24, %25, %26, %27, %28, %29, %30, %31}, {%32, %33, %34, %35}, db, 0, 1, 1, %37;\n}\n"
    : "=f"(d[0]), "=f"(d[1]), "=f"(d[2]), "=f"(d[3]), "=f"(d[4]), "=f"(d[5]), "=f"(d[6]), "=f"(d[7]), "=f"(d[8]), "=f"(d[9]), "=f"(d[10]), "=f"(d[11]), "=f"(d[12]), "=f"(d[13]), "=f"(d[14]), "=f"(d[15]), "=f"(d[16]), "=f"(d[17]), "=f"(d[18]), "=f"(d[19]), "=f"(d[20]), "=f"(d[21]), "=f"(d[22]), "=f"(d[23]), "=f"(d[24]), "=f"(d[25]), "=f"(d[26]), "=f"(d[27]), "=f"(d[28]), "=f"(d[29]), "=f"(d[30]), "=f"(d[31])
    : "r"(a0), "r"(a1), "r"(a2), "r"(a3), "r"(blo), "n"(TB), "n"(BOFF), "n"(BHI));
}

template<int TB, uint32_t BOFF, uint32_t BHI, int SD>
__device__ __forceinline__ void wgmma_rs_128(float* d, uint32_t a0, uint32_t a1, uint32_t a2, uint32_t a3, uint32_t blo) {
  if constexpr (SD) asm volatile("{\n.reg .b32 tb;\n.reg .b64 db;\n"
    "add.u32 tb, %68, %70;\nmov.b64 db, {tb, %71};\n"
    "wgmma.mma_async.sync.aligned.m64n128k16.f32.bf16.bf16 {%0, %1, %2, %3, %4, %5, %6, %7, %8, %9, %10, %11, %12, %13, %14, %15, %16, %17, %18, %19, %20, %21, %22, %23, %24, %25, %26, %27, %28, %29, %30, %31, %32, %33, %34, %35, %36, %37, %38, %39, %40, %41, %42, %43, %44, %45, %46, %47, %48, %49, %50, %51, %52, %53, %54, %55, %56, %57, %58, %59, %60, %61, %62, %63}, {%64, %65, %66, %67}, db, 1, 1, 1, %69;\n}\n"
    : "+f"(d[0]), "+f"(d[1]), "+f"(d[2]), "+f"(d[3]), "+f"(d[4]), "+f"(d[5]), "+f"(d[6]), "+f"(d[7]), "+f"(d[8]), "+f"(d[9]), "+f"(d[10]), "+f"(d[11]), "+f"(d[12]), "+f"(d[13]), "+f"(d[14]), "+f"(d[15]), "+f"(d[16]), "+f"(d[17]), "+f"(d[18]), "+f"(d[19]), "+f"(d[20]), "+f"(d[21]), "+f"(d[22]), "+f"(d[23]), "+f"(d[24]), "+f"(d[25]), "+f"(d[26]), "+f"(d[27]), "+f"(d[28]), "+f"(d[29]), "+f"(d[30]), "+f"(d[31]), "+f"(d[32]), "+f"(d[33]), "+f"(d[34]), "+f"(d[35]), "+f"(d[36]), "+f"(d[37]), "+f"(d[38]), "+f"(d[39]), "+f"(d[40]), "+f"(d[41]), "+f"(d[42]), "+f"(d[43]), "+f"(d[44]), "+f"(d[45]), "+f"(d[46]), "+f"(d[47]), "+f"(d[48]), "+f"(d[49]), "+f"(d[50]), "+f"(d[51]), "+f"(d[52]), "+f"(d[53]), "+f"(d[54]), "+f"(d[55]), "+f"(d[56]), "+f"(d[57]), "+f"(d[58]), "+f"(d[59]), "+f"(d[60]), "+f"(d[61]), "+f"(d[62]), "+f"(d[63])
    : "r"(a0), "r"(a1), "r"(a2), "r"(a3), "r"(blo), "n"(TB), "n"(BOFF), "n"(BHI));
  else asm volatile("{\n.reg .b32 tb;\n.reg .b64 db;\n"
    "add.u32 tb, %68, %70;\nmov.b64 db, {tb, %71};\n"
    "wgmma.mma_async.sync.aligned.m64n128k16.f32.bf16.bf16 {%0, %1, %2, %3, %4, %5, %6, %7, %8, %9, %10, %11, %12, %13, %14, %15, %16, %17, %18, %19, %20, %21, %22, %23, %24, %25, %26, %27, %28, %29, %30, %31, %32, %33, %34, %35, %36, %37, %38, %39, %40, %41, %42, %43, %44, %45, %46, %47, %48, %49, %50, %51, %52, %53, %54, %55, %56, %57, %58, %59, %60, %61, %62, %63}, {%64, %65, %66, %67}, db, 0, 1, 1, %69;\n}\n"
    : "=f"(d[0]), "=f"(d[1]), "=f"(d[2]), "=f"(d[3]), "=f"(d[4]), "=f"(d[5]), "=f"(d[6]), "=f"(d[7]), "=f"(d[8]), "=f"(d[9]), "=f"(d[10]), "=f"(d[11]), "=f"(d[12]), "=f"(d[13]), "=f"(d[14]), "=f"(d[15]), "=f"(d[16]), "=f"(d[17]), "=f"(d[18]), "=f"(d[19]), "=f"(d[20]), "=f"(d[21]), "=f"(d[22]), "=f"(d[23]), "=f"(d[24]), "=f"(d[25]), "=f"(d[26]), "=f"(d[27]), "=f"(d[28]), "=f"(d[29]), "=f"(d[30]), "=f"(d[31]), "=f"(d[32]), "=f"(d[33]), "=f"(d[34]), "=f"(d[35]), "=f"(d[36]), "=f"(d[37]), "=f"(d[38]), "=f"(d[39]), "=f"(d[40]), "=f"(d[41]), "=f"(d[42]), "=f"(d[43]), "=f"(d[44]), "=f"(d[45]), "=f"(d[46]), "=f"(d[47]), "=f"(d[48]), "=f"(d[49]), "=f"(d[50]), "=f"(d[51]), "=f"(d[52]), "=f"(d[53]), "=f"(d[54]), "=f"(d[55]), "=f"(d[56]), "=f"(d[57]), "=f"(d[58]), "=f"(d[59]), "=f"(d[60]), "=f"(d[61]), "=f"(d[62]), "=f"(d[63])
    : "r"(a0), "r"(a1), "r"(a2), "r"(a3), "r"(blo), "n"(TB), "n"(BOFF), "n"(BHI));
}

template<int TA, int TB, uint32_t AOFF, uint32_t AHI, uint32_t BOFF, uint32_t BHI, int SD>
__device__ __forceinline__ void wgmma_ss_128(float* d, uint32_t alo, uint32_t blo) {
  if constexpr (SD) asm volatile("{\n.reg .b32 ta, tb;\n.reg .b64 da, db;\n"
    "add.u32 ta, %64, %68;\nmov.b64 da, {ta, %69};\nadd.u32 tb, %65, %70;\nmov.b64 db, {tb, %71};\n"
    "wgmma.mma_async.sync.aligned.m64n128k16.f32.bf16.bf16 {%0, %1, %2, %3, %4, %5, %6, %7, %8, %9, %10, %11, %12, %13, %14, %15, %16, %17, %18, %19, %20, %21, %22, %23, %24, %25, %26, %27, %28, %29, %30, %31, %32, %33, %34, %35, %36, %37, %38, %39, %40, %41, %42, %43, %44, %45, %46, %47, %48, %49, %50, %51, %52, %53, %54, %55, %56, %57, %58, %59, %60, %61, %62, %63}, da, db, 1, 1, 1, %66, %67;\n}\n"
    : "+f"(d[0]), "+f"(d[1]), "+f"(d[2]), "+f"(d[3]), "+f"(d[4]), "+f"(d[5]), "+f"(d[6]), "+f"(d[7]), "+f"(d[8]), "+f"(d[9]), "+f"(d[10]), "+f"(d[11]), "+f"(d[12]), "+f"(d[13]), "+f"(d[14]), "+f"(d[15]), "+f"(d[16]), "+f"(d[17]), "+f"(d[18]), "+f"(d[19]), "+f"(d[20]), "+f"(d[21]), "+f"(d[22]), "+f"(d[23]), "+f"(d[24]), "+f"(d[25]), "+f"(d[26]), "+f"(d[27]), "+f"(d[28]), "+f"(d[29]), "+f"(d[30]), "+f"(d[31]), "+f"(d[32]), "+f"(d[33]), "+f"(d[34]), "+f"(d[35]), "+f"(d[36]), "+f"(d[37]), "+f"(d[38]), "+f"(d[39]), "+f"(d[40]), "+f"(d[41]), "+f"(d[42]), "+f"(d[43]), "+f"(d[44]), "+f"(d[45]), "+f"(d[46]), "+f"(d[47]), "+f"(d[48]), "+f"(d[49]), "+f"(d[50]), "+f"(d[51]), "+f"(d[52]), "+f"(d[53]), "+f"(d[54]), "+f"(d[55]), "+f"(d[56]), "+f"(d[57]), "+f"(d[58]), "+f"(d[59]), "+f"(d[60]), "+f"(d[61]), "+f"(d[62]), "+f"(d[63])
    : "r"(alo), "r"(blo), "n"(TA), "n"(TB), "n"(AOFF), "n"(AHI), "n"(BOFF), "n"(BHI));
  else asm volatile("{\n.reg .b32 ta, tb;\n.reg .b64 da, db;\n"
    "add.u32 ta, %64, %68;\nmov.b64 da, {ta, %69};\nadd.u32 tb, %65, %70;\nmov.b64 db, {tb, %71};\n"
    "wgmma.mma_async.sync.aligned.m64n128k16.f32.bf16.bf16 {%0, %1, %2, %3, %4, %5, %6, %7, %8, %9, %10, %11, %12, %13, %14, %15, %16, %17, %18, %19, %20, %21, %22, %23, %24, %25, %26, %27, %28, %29, %30, %31, %32, %33, %34, %35, %36, %37, %38, %39, %40, %41, %42, %43, %44, %45, %46, %47, %48, %49, %50, %51, %52, %53, %54, %55, %56, %57, %58, %59, %60, %61, %62, %63}, da, db, 0, 1, 1, %66, %67;\n}\n"
    : "=f"(d[0]), "=f"(d[1]), "=f"(d[2]), "=f"(d[3]), "=f"(d[4]), "=f"(d[5]), "=f"(d[6]), "=f"(d[7]), "=f"(d[8]), "=f"(d[9]), "=f"(d[10]), "=f"(d[11]), "=f"(d[12]), "=f"(d[13]), "=f"(d[14]), "=f"(d[15]), "=f"(d[16]), "=f"(d[17]), "=f"(d[18]), "=f"(d[19]), "=f"(d[20]), "=f"(d[21]), "=f"(d[22]), "=f"(d[23]), "=f"(d[24]), "=f"(d[25]), "=f"(d[26]), "=f"(d[27]), "=f"(d[28]), "=f"(d[29]), "=f"(d[30]), "=f"(d[31]), "=f"(d[32]), "=f"(d[33]), "=f"(d[34]), "=f"(d[35]), "=f"(d[36]), "=f"(d[37]), "=f"(d[38]), "=f"(d[39]), "=f"(d[40]), "=f"(d[41]), "=f"(d[42]), "=f"(d[43]), "=f"(d[44]), "=f"(d[45]), "=f"(d[46]), "=f"(d[47]), "=f"(d[48]), "=f"(d[49]), "=f"(d[50]), "=f"(d[51]), "=f"(d[52]), "=f"(d[53]), "=f"(d[54]), "=f"(d[55]), "=f"(d[56]), "=f"(d[57]), "=f"(d[58]), "=f"(d[59]), "=f"(d[60]), "=f"(d[61]), "=f"(d[62]), "=f"(d[63])
    : "r"(alo), "r"(blo), "n"(TA), "n"(TB), "n"(AOFF), "n"(AHI), "n"(BOFF), "n"(BHI));
}

template<int TA, int TB, uint32_t AOFF, uint32_t AHI, uint32_t BOFF, uint32_t BHI, int SD>
__device__ __forceinline__ void wgmma_ss_16(float* d, uint32_t alo, uint32_t blo) {
  if constexpr (SD) asm volatile("{\n.reg .b32 ta, tb;\n.reg .b64 da, db;\n"
    "add.u32 ta, %8, %12;\nmov.b64 da, {ta, %13};\nadd.u32 tb, %9, %14;\nmov.b64 db, {tb, %15};\n"
    "wgmma.mma_async.sync.aligned.m64n16k16.f32.bf16.bf16 {%0, %1, %2, %3, %4, %5, %6, %7}, da, db, 1, 1, 1, %10, %11;\n}\n"
    : "+f"(d[0]), "+f"(d[1]), "+f"(d[2]), "+f"(d[3]), "+f"(d[4]), "+f"(d[5]), "+f"(d[6]), "+f"(d[7])
    : "r"(alo), "r"(blo), "n"(TA), "n"(TB), "n"(AOFF), "n"(AHI), "n"(BOFF), "n"(BHI));
  else asm volatile("{\n.reg .b32 ta, tb;\n.reg .b64 da, db;\n"
    "add.u32 ta, %8, %12;\nmov.b64 da, {ta, %13};\nadd.u32 tb, %9, %14;\nmov.b64 db, {tb, %15};\n"
    "wgmma.mma_async.sync.aligned.m64n16k16.f32.bf16.bf16 {%0, %1, %2, %3, %4, %5, %6, %7}, da, db, 0, 1, 1, %10, %11;\n}\n"
    : "=f"(d[0]), "=f"(d[1]), "=f"(d[2]), "=f"(d[3]), "=f"(d[4]), "=f"(d[5]), "=f"(d[6]), "=f"(d[7])
    : "r"(alo), "r"(blo), "n"(TA), "n"(TB), "n"(AOFF), "n"(AHI), "n"(BOFF), "n"(BHI));
}

template<int TA, int TB, uint32_t AOFF, uint32_t AHI, uint32_t BOFF, uint32_t BHI>
__device__ __forceinline__ void wgmma_ssp_128(float* d, uint32_t alo, uint32_t blo, int sd) {
  asm volatile("{\n.reg .pred p;\n.reg .b32 ta, tb;\n.reg .b64 da, db;\nsetp.ne.b32 p, %72, 0;\n"
    "add.u32 ta, %64, %68;\nmov.b64 da, {ta, %69};\nadd.u32 tb, %65, %70;\nmov.b64 db, {tb, %71};\n"
    "wgmma.mma_async.sync.aligned.m64n128k16.f32.bf16.bf16 {%0, %1, %2, %3, %4, %5, %6, %7, %8, %9, %10, %11, %12, %13, %14, %15, %16, %17, %18, %19, %20, %21, %22, %23, %24, %25, %26, %27, %28, %29, %30, %31, %32, %33, %34, %35, %36, %37, %38, %39, %40, %41, %42, %43, %44, %45, %46, %47, %48, %49, %50, %51, %52, %53, %54, %55, %56, %57, %58, %59, %60, %61, %62, %63}, da, db, p, 1, 1, %66, %67;\n}\n"
    : "+f"(d[0]), "+f"(d[1]), "+f"(d[2]), "+f"(d[3]), "+f"(d[4]), "+f"(d[5]), "+f"(d[6]), "+f"(d[7]), "+f"(d[8]), "+f"(d[9]), "+f"(d[10]), "+f"(d[11]), "+f"(d[12]), "+f"(d[13]), "+f"(d[14]), "+f"(d[15]), "+f"(d[16]), "+f"(d[17]), "+f"(d[18]), "+f"(d[19]), "+f"(d[20]), "+f"(d[21]), "+f"(d[22]), "+f"(d[23]), "+f"(d[24]), "+f"(d[25]), "+f"(d[26]), "+f"(d[27]), "+f"(d[28]), "+f"(d[29]), "+f"(d[30]), "+f"(d[31]), "+f"(d[32]), "+f"(d[33]), "+f"(d[34]), "+f"(d[35]), "+f"(d[36]), "+f"(d[37]), "+f"(d[38]), "+f"(d[39]), "+f"(d[40]), "+f"(d[41]), "+f"(d[42]), "+f"(d[43]), "+f"(d[44]), "+f"(d[45]), "+f"(d[46]), "+f"(d[47]), "+f"(d[48]), "+f"(d[49]), "+f"(d[50]), "+f"(d[51]), "+f"(d[52]), "+f"(d[53]), "+f"(d[54]), "+f"(d[55]), "+f"(d[56]), "+f"(d[57]), "+f"(d[58]), "+f"(d[59]), "+f"(d[60]), "+f"(d[61]), "+f"(d[62]), "+f"(d[63])
    : "r"(alo), "r"(blo), "n"(TA), "n"(TB), "n"(AOFF), "n"(AHI), "n"(BOFF), "n"(BHI), "r"(sd));
}

__device__ __forceinline__ void place_h(uint32_t* h, const uint32_t* g, const uint32_t* u, int c) {
  asm volatile("{\n.reg .pred p;\n"
    "setp.ge.s32 p, %160, 4;\n@p bra.uni PH4;\nsetp.ge.s32 p, %160, 2;\n@p bra.uni PH2;\nsetp.eq.s32 p, %160, 1;\n@p bra.uni PH1;\n"
    "mul.rn.bf16x2 %0, %128, %144;\nmul.rn.bf16x2 %1, %129, %145;\nmul.rn.bf16x2 %2, %130, %146;\nmul.rn.bf16x2 %3, %131, %147;\nmul.rn.bf16x2 %4, %132, %148;\nmul.rn.bf16x2 %5, %133, %149;\nmul.rn.bf16x2 %6, %134, %150;\nmul.rn.bf16x2 %7, %135, %151;\nmul.rn.bf16x2 %8, %136, %152;\nmul.rn.bf16x2 %9, %137, %153;\nmul.rn.bf16x2 %10, %138, %154;\nmul.rn.bf16x2 %11, %139, %155;\nmul.rn.bf16x2 %12, %140, %156;\nmul.rn.bf16x2 %13, %141, %157;\nmul.rn.bf16x2 %14, %142, %158;\nmul.rn.bf16x2 %15, %143, %159;\nbra.uni PHE;\n"
    "PH1:\nmul.rn.bf16x2 %16, %128, %144;\nmul.rn.bf16x2 %17, %129, %145;\nmul.rn.bf16x2 %18, %130, %146;\nmul.rn.bf16x2 %19, %131, %147;\nmul.rn.bf16x2 %20, %132, %148;\nmul.rn.bf16x2 %21, %133, %149;\nmul.rn.bf16x2 %22, %134, %150;\nmul.rn.bf16x2 %23, %135, %151;\nmul.rn.bf16x2 %24, %136, %152;\nmul.rn.bf16x2 %25, %137, %153;\nmul.rn.bf16x2 %26, %138, %154;\nmul.rn.bf16x2 %27, %139, %155;\nmul.rn.bf16x2 %28, %140, %156;\nmul.rn.bf16x2 %29, %141, %157;\nmul.rn.bf16x2 %30, %142, %158;\nmul.rn.bf16x2 %31, %143, %159;\nbra.uni PHE;\n"
    "PH2:\nsetp.eq.s32 p, %160, 3;\n@p bra.uni PH3;\nmul.rn.bf16x2 %32, %128, %144;\nmul.rn.bf16x2 %33, %129, %145;\nmul.rn.bf16x2 %34, %130, %146;\nmul.rn.bf16x2 %35, %131, %147;\nmul.rn.bf16x2 %36, %132, %148;\nmul.rn.bf16x2 %37, %133, %149;\nmul.rn.bf16x2 %38, %134, %150;\nmul.rn.bf16x2 %39, %135, %151;\nmul.rn.bf16x2 %40, %136, %152;\nmul.rn.bf16x2 %41, %137, %153;\nmul.rn.bf16x2 %42, %138, %154;\nmul.rn.bf16x2 %43, %139, %155;\nmul.rn.bf16x2 %44, %140, %156;\nmul.rn.bf16x2 %45, %141, %157;\nmul.rn.bf16x2 %46, %142, %158;\nmul.rn.bf16x2 %47, %143, %159;\nbra.uni PHE;\n"
    "PH3:\nmul.rn.bf16x2 %48, %128, %144;\nmul.rn.bf16x2 %49, %129, %145;\nmul.rn.bf16x2 %50, %130, %146;\nmul.rn.bf16x2 %51, %131, %147;\nmul.rn.bf16x2 %52, %132, %148;\nmul.rn.bf16x2 %53, %133, %149;\nmul.rn.bf16x2 %54, %134, %150;\nmul.rn.bf16x2 %55, %135, %151;\nmul.rn.bf16x2 %56, %136, %152;\nmul.rn.bf16x2 %57, %137, %153;\nmul.rn.bf16x2 %58, %138, %154;\nmul.rn.bf16x2 %59, %139, %155;\nmul.rn.bf16x2 %60, %140, %156;\nmul.rn.bf16x2 %61, %141, %157;\nmul.rn.bf16x2 %62, %142, %158;\nmul.rn.bf16x2 %63, %143, %159;\nbra.uni PHE;\n"
    "PH4:\nsetp.ge.s32 p, %160, 6;\n@p bra.uni PH6;\nsetp.eq.s32 p, %160, 5;\n@p bra.uni PH5;\nmul.rn.bf16x2 %64, %128, %144;\nmul.rn.bf16x2 %65, %129, %145;\nmul.rn.bf16x2 %66, %130, %146;\nmul.rn.bf16x2 %67, %131, %147;\nmul.rn.bf16x2 %68, %132, %148;\nmul.rn.bf16x2 %69, %133, %149;\nmul.rn.bf16x2 %70, %134, %150;\nmul.rn.bf16x2 %71, %135, %151;\nmul.rn.bf16x2 %72, %136, %152;\nmul.rn.bf16x2 %73, %137, %153;\nmul.rn.bf16x2 %74, %138, %154;\nmul.rn.bf16x2 %75, %139, %155;\nmul.rn.bf16x2 %76, %140, %156;\nmul.rn.bf16x2 %77, %141, %157;\nmul.rn.bf16x2 %78, %142, %158;\nmul.rn.bf16x2 %79, %143, %159;\nbra.uni PHE;\n"
    "PH5:\nmul.rn.bf16x2 %80, %128, %144;\nmul.rn.bf16x2 %81, %129, %145;\nmul.rn.bf16x2 %82, %130, %146;\nmul.rn.bf16x2 %83, %131, %147;\nmul.rn.bf16x2 %84, %132, %148;\nmul.rn.bf16x2 %85, %133, %149;\nmul.rn.bf16x2 %86, %134, %150;\nmul.rn.bf16x2 %87, %135, %151;\nmul.rn.bf16x2 %88, %136, %152;\nmul.rn.bf16x2 %89, %137, %153;\nmul.rn.bf16x2 %90, %138, %154;\nmul.rn.bf16x2 %91, %139, %155;\nmul.rn.bf16x2 %92, %140, %156;\nmul.rn.bf16x2 %93, %141, %157;\nmul.rn.bf16x2 %94, %142, %158;\nmul.rn.bf16x2 %95, %143, %159;\nbra.uni PHE;\n"
    "PH6:\nsetp.eq.s32 p, %160, 7;\n@p bra.uni PH7;\nmul.rn.bf16x2 %96, %128, %144;\nmul.rn.bf16x2 %97, %129, %145;\nmul.rn.bf16x2 %98, %130, %146;\nmul.rn.bf16x2 %99, %131, %147;\nmul.rn.bf16x2 %100, %132, %148;\nmul.rn.bf16x2 %101, %133, %149;\nmul.rn.bf16x2 %102, %134, %150;\nmul.rn.bf16x2 %103, %135, %151;\nmul.rn.bf16x2 %104, %136, %152;\nmul.rn.bf16x2 %105, %137, %153;\nmul.rn.bf16x2 %106, %138, %154;\nmul.rn.bf16x2 %107, %139, %155;\nmul.rn.bf16x2 %108, %140, %156;\nmul.rn.bf16x2 %109, %141, %157;\nmul.rn.bf16x2 %110, %142, %158;\nmul.rn.bf16x2 %111, %143, %159;\nbra.uni PHE;\n"
    "PH7:\nmul.rn.bf16x2 %112, %128, %144;\nmul.rn.bf16x2 %113, %129, %145;\nmul.rn.bf16x2 %114, %130, %146;\nmul.rn.bf16x2 %115, %131, %147;\nmul.rn.bf16x2 %116, %132, %148;\nmul.rn.bf16x2 %117, %133, %149;\nmul.rn.bf16x2 %118, %134, %150;\nmul.rn.bf16x2 %119, %135, %151;\nmul.rn.bf16x2 %120, %136, %152;\nmul.rn.bf16x2 %121, %137, %153;\nmul.rn.bf16x2 %122, %138, %154;\nmul.rn.bf16x2 %123, %139, %155;\nmul.rn.bf16x2 %124, %140, %156;\nmul.rn.bf16x2 %125, %141, %157;\nmul.rn.bf16x2 %126, %142, %158;\nmul.rn.bf16x2 %127, %143, %159;\n"
    "PHE:\n}\n"
    : "+r"(h[0]), "+r"(h[1]), "+r"(h[2]), "+r"(h[3]), "+r"(h[4]), "+r"(h[5]), "+r"(h[6]), "+r"(h[7]), "+r"(h[8]), "+r"(h[9]), "+r"(h[10]), "+r"(h[11]), "+r"(h[12]), "+r"(h[13]), "+r"(h[14]), "+r"(h[15]), "+r"(h[16]), "+r"(h[17]), "+r"(h[18]), "+r"(h[19]), "+r"(h[20]), "+r"(h[21]), "+r"(h[22]), "+r"(h[23]), "+r"(h[24]), "+r"(h[25]), "+r"(h[26]), "+r"(h[27]), "+r"(h[28]), "+r"(h[29]), "+r"(h[30]), "+r"(h[31]), "+r"(h[32]), "+r"(h[33]), "+r"(h[34]), "+r"(h[35]), "+r"(h[36]), "+r"(h[37]), "+r"(h[38]), "+r"(h[39]), "+r"(h[40]), "+r"(h[41]), "+r"(h[42]), "+r"(h[43]), "+r"(h[44]), "+r"(h[45]), "+r"(h[46]), "+r"(h[47]), "+r"(h[48]), "+r"(h[49]), "+r"(h[50]), "+r"(h[51]), "+r"(h[52]), "+r"(h[53]), "+r"(h[54]), "+r"(h[55]), "+r"(h[56]), "+r"(h[57]), "+r"(h[58]), "+r"(h[59]), "+r"(h[60]), "+r"(h[61]), "+r"(h[62]), "+r"(h[63]), "+r"(h[64]), "+r"(h[65]), "+r"(h[66]), "+r"(h[67]), "+r"(h[68]), "+r"(h[69]), "+r"(h[70]), "+r"(h[71]), "+r"(h[72]), "+r"(h[73]), "+r"(h[74]), "+r"(h[75]), "+r"(h[76]), "+r"(h[77]), "+r"(h[78]), "+r"(h[79]), "+r"(h[80]), "+r"(h[81]), "+r"(h[82]), "+r"(h[83]), "+r"(h[84]), "+r"(h[85]), "+r"(h[86]), "+r"(h[87]), "+r"(h[88]), "+r"(h[89]), "+r"(h[90]), "+r"(h[91]), "+r"(h[92]), "+r"(h[93]), "+r"(h[94]), "+r"(h[95]), "+r"(h[96]), "+r"(h[97]), "+r"(h[98]), "+r"(h[99]), "+r"(h[100]), "+r"(h[101]), "+r"(h[102]), "+r"(h[103]), "+r"(h[104]), "+r"(h[105]), "+r"(h[106]), "+r"(h[107]), "+r"(h[108]), "+r"(h[109]), "+r"(h[110]), "+r"(h[111]), "+r"(h[112]), "+r"(h[113]), "+r"(h[114]), "+r"(h[115]), "+r"(h[116]), "+r"(h[117]), "+r"(h[118]), "+r"(h[119]), "+r"(h[120]), "+r"(h[121]), "+r"(h[122]), "+r"(h[123]), "+r"(h[124]), "+r"(h[125]), "+r"(h[126]), "+r"(h[127])
    : "r"(g[0]), "r"(g[1]), "r"(g[2]), "r"(g[3]), "r"(g[4]), "r"(g[5]), "r"(g[6]), "r"(g[7]), "r"(g[8]), "r"(g[9]), "r"(g[10]), "r"(g[11]), "r"(g[12]), "r"(g[13]), "r"(g[14]), "r"(g[15]), "r"(u[0]), "r"(u[1]), "r"(u[2]), "r"(u[3]), "r"(u[4]), "r"(u[5]), "r"(u[6]), "r"(u[7]), "r"(u[8]), "r"(u[9]), "r"(u[10]), "r"(u[11]), "r"(u[12]), "r"(u[13]), "r"(u[14]), "r"(u[15]), "r"(c));
}

constexpr int SM_A = 0;
constexpr int A_HALF = 576 * 128;
constexpr int SM_RING = 2 * A_HALF;
constexpr int NSTG = 9, STG = 8192;
#define LAG 2
#define CUT 7
#define KEEP 5
#define PACE 200
#define SPR 2
#define SLK 0
#define SLU 0
#define PCE 1
#define ZSL 80
#define ORDER 1
#define WD 2
constexpr int SM_CS = SM_RING + NSTG * STG;
constexpr int SM_ZERO = SM_CS + 4096;
constexpr int P_LN = SM_CS;
constexpr int P_KC = P_LN + 768, KC_SZ = 1792;
constexpr int SM_ONE = SM_CS + 6144;
constexpr int SM_R2 = SM_ONE + 256;
constexpr int SM_MU = SM_R2 + 512;
constexpr int P_SC = SM_MU + 512;
constexpr int SM_BAR = P_SC + 72;
constexpr int B_FULL = SM_BAR, B_EMPTY = B_FULL + 72, B_A = B_EMPTY + 72, B_CS = B_A + 144, B_STAGED = B_CS + 8,
              B_STFREE = B_STAGED + 48, B_IN = B_STFREE + 8, B_P1 = B_IN + 8, B_U = B_P1 + 8, B_MU = B_U + 8, B_R2 = B_MU + 8, B_RES = B_R2 + 8,
              B_X = B_RES + 8, B_T = B_X + 8, B_E = B_T + 16, B_HD = B_E + 8;
constexpr int B_CSD = B_HD + 8, B_CSL = B_HD + 16, B_XD = B_HD + 24, B_EF = B_HD + 32, B_KD = B_HD + 56;
constexpr int SM_PROF = B_HD + 72;
constexpr int SM_TOTAL = SM_PROF + 640;
static_assert(SM_TOTAL <= 232448, "smem");

struct Maps { CUtensorMap hT, wg, wu, wd, out, E, U, X; };
struct Prm { const __nv_bfloat16* x; Scratch* scr; const __nv_bfloat16 *logdt, *Dskip, *ssm[6], *Wg, *Wu, *Wd; };

constexpr int T_SZ = 7168, T_B2 = 3040, T_B3 = T_B2 + 2048, T_USED = T_B3 + 2048;
constexpr int PW_SZ = 4224, PP_SZ = 2 * PW_SZ;
constexpr int S_Z1 = 128, S_Z2 = S_Z1 + 3200, S_Y1 = S_Z2 + 3072, S_Y2 = S_Y1 + 2048, S_SZ = S_Y2 + 2176;
constexpr int P_T2 = T_SZ, P_P2 = 2 * T_SZ, P_S2 = A_HALF + 8192, P_S0 = 24576;
constexpr int P_US = 35840, P_U0 = P_US + 3072;
constexpr int P_T3 = P_U0 + 16384, P_UE = P_T3 + 2 * T_SZ;
constexpr int P_XS = A_HALF + 35840, P_X0 = P_XS, P_P0 = P_X0 + 16384, P_XE = P_P0 + 2 * PP_SZ;
constexpr int P_XR = SM_RING + 32768, P_CW = SM_RING + 52224, P_PZ = SM_RING + 65536;
static_assert(P_P2 + PP_SZ <= P_S0 && P_S0 + S_SZ <= P_US && P_UE + 4096 <= A_HALF && T_USED + 32 <= T_SZ && P_XE % 128 == 0 &&
              P_XE + 4096 <= SM_RING && P_P2 % 128 == 0, "pre-phase map");

struct cf { float r, i; };
__device__ __forceinline__ cf cmul(cf a, cf b) { return {fmaf(a.r, b.r, -a.i * b.i), fmaf(a.r, b.i, a.i * b.r)}; }
__device__ __forceinline__ cf cexp_n(float zr2, float zt, float e) {
  float mag, s, c;
  asm("ex2.approx.ftz.f32 %0, %1;" : "=f"(mag) : "f"(zr2 * e));
  const float t = zt * e, f = (t - rintf(t)) * 6.283185307179586f;
  asm("sin.approx.ftz.f32 %0, %1;" : "=f"(s) : "f"(f));
  asm("cos.approx.ftz.f32 %0, %1;" : "=f"(c) : "f"(f));
  return {mag * c, mag * s};
}
__device__ __forceinline__ void st_chunk(uint32_t addr, const cf* v) {
  sts128(addr, pack_bf16(v[0].r, v[1].r), pack_bf16(v[2].r, v[3].r), pack_bf16(v[4].r, v[5].r), pack_bf16(v[6].r, v[7].r));
  sts128(addr + 2048, pack_bf16(v[0].i, v[1].i), pack_bf16(v[2].i, v[3].i), pack_bf16(v[4].i, v[5].i), pack_bf16(v[6].i, v[7].i));
}
__device__ __forceinline__ void mma16816(float* c, uint32_t a0, uint32_t a1, uint32_t a2, uint32_t a3, uint32_t b0, uint32_t b1) {
  asm volatile("mma.sync.aligned.m16n8k16.row.col.f32.bf16.bf16.f32 {%0,%1,%2,%3}, {%4,%5,%6,%7}, {%8,%9}, {%0,%1,%2,%3};"
    : "+f"(c[0]), "+f"(c[1]), "+f"(c[2]), "+f"(c[3]) : "r"(a0), "r"(a1), "r"(a2), "r"(a3), "r"(b0), "r"(b1));
}
__device__ __forceinline__ uint4 ld_piece(const uint4* p) {
  uint4 v;
  asm volatile("{\n.reg .b128 t;\nld.relaxed.gpu.global.b128 t, [%4];\nmov.b128 {%0, %1, %2, %3}, t;\n}" : "=r"(v.x), "=r"(v.y), "=r"(v.z), "=r"(v.w) : "l"(p) : "memory");
  return v;
}
__device__ __forceinline__ void st_piece(void* p, uint32_t a, uint32_t b, uint32_t c, uint32_t d) {
  asm volatile("{\n.reg .b128 t;\nmov.b128 t, {%1, %2, %3, %4};\nst.relaxed.gpu.global.b128 [%0], t;\n}" :: "l"(p), "r"(a), "r"(b), "r"(c), "r"(d) : "memory");
}
template<int STRIDE> __device__ __forceinline__ void ld_pieces(uint4* v, const char* base, uint32_t off) {
  #pragma unroll
  for (int i = 0; i < 4; i++) v[i] = ld_piece((const uint4*)(base + off + i * STRIDE));
}
template<int STRIDE> __device__ __forceinline__ void fix_pieces(uint4* v, const char* base, uint32_t off) {
  int it = 0;
  #pragma unroll 1
  while (!__all_sync(~0u, v[0].x & v[1].x & v[2].x & v[3].x & 1)) {
    ld_pieces<STRIDE>(v, base, off);
    if (++it > (1 << 22)) __trap();
  }
}

template<bool EVEN, int S0, int S1, bool DRAIN>
__device__ __forceinline__ void p2_step(uint32_t sb, uint32_t ebar, bool arr, int st, const uint32_t* h, float* cur, float* prev,
                                        uint32_t toff, int wg, int fs, int mt, uint4* g_part) {
  constexpr uint32_t ph = EVEN ? 0 : 1;
  const bool rel = arr && st < 8;
  char* dst = (char*)g_part + (size_t)(((mt * 9 + (st == 1 ? 8 : ((fs + st - 1) & 7))) * 3 + (st >= 7 ? st - 6 : 0)) * 2 + wg) * 8192 + toff;
  sfor<S0, S1>([&](auto S) {
    constexpr int s = S.v;
    mbar_wait(sb + B_FULL + 8 * s, ph);
    wg_fence();
    sfor<0, 4>([&](auto KK) {
      constexpr int kk = KK.v, i = (s * 4 + kk) * 4;
      wgmma_rs_64<1, desc_lo(SM_RING + s * STG + kk * 2048, 4096), DESC_HI_128, ((s + kk) > 0)>(cur, h[i], h[i + 1], h[i + 2], h[i + 3], 0);
    });
    wg_commit();
    if (DRAIN) return;
    if (s == 0) {
      wg_wait<1>();
      keep<32>(prev);
      if (arr && (!EVEN || st > 0)) { mbar_arrive_cl(ebar + 8 * (NSTG - 2)); mbar_arrive_cl(ebar + 8 * (NSTG - 1)); }
    } else if (s >= 2) {
      wg_wait<2>();
      if (rel) mbar_arrive_cl(ebar + 8 * (s >= 2 ? s - 2 : 0));
    }
    auto piece = [&](auto I) {
      constexpr int i = I.v;
      const uint32_t p0 = pack_bf16(prev[8 * i], prev[8 * i + 1]), p1 = pack_bf16(prev[8 * i + 2], prev[8 * i + 3]);
      const uint32_t p2 = pack_bf16(prev[8 * i + 4], prev[8 * i + 5]), p3 = pack_bf16(prev[8 * i + 6], prev[8 * i + 7]);
      if (st < 7) {
        if (i == 0 && st == 1) mbar_wait(sb + B_STFREE, 0);
        asm volatile("red.relaxed.gpu.global.add.noftz.v4.bf16x2 [%0], {%1, %2, %3, %4};" :: "l"(dst + i * 512), "r"(p0), "r"(p1), "r"(p2), "r"(p3) : "memory");
        if (i == 3) mbar_arrive(sb + B_STAGED + 8 * (st - 1));
      } else st_piece(dst + i * 512, p0 | 1u, p1, p2, p3);
    };
    if (s == 1 || s == 3) { if (!EVEN || st > 0) piece(IC<(s == 3)>{}); }
    if (s == 5 || s == 7) { if (!EVEN || (st > 0 && st < 8)) piece(IC<(s == 7 ? 3 : 2)>{}); }
    if (EVEN && (s == 2 || s == 4)) { if (st == 8) piece(IC<(s == 4 ? 3 : 2)>{}); }
  });
}

__global__ void __cluster_dims__(2, 1, 1) __launch_bounds__(384, 1)
fused_kernel(const __grid_constant__ Prm prm, __nv_bfloat16* __restrict__ out, const __grid_constant__ Maps maps) {
  extern __shared__ __align__(1024) uint8_t smem_raw[];
  const uint32_t sb = smem_u32(smem_raw);
  int warp = __shfl_sync(~0u, (int)(threadIdx.x >> 5), 0);
  int lane = threadIdx.x & 31;
  const int cta = blockIdx.x;
  const uint32_t rank = cta & 1;
  const int pair = cta >> 1;
  const int fs = pair & 7;
  const int mt = (pair >> 3) * 2 + rank;
  PROF_INIT();
  if (warp == 0) { STAMP(0); GST32(38); }
  if (warp == 10) GSTAMP(PROF_SLOTS - 2);
  unsigned epoch;
  const int grpm = (rank << 6) | pair;
  const int chm = 32 * (grpm >> 5) + 8 * ((grpm & 7) >> 1) + 2 * ((grpm >> 3) & 3) + (grpm & 1);
  {
    const int wg = warp >> 2, wq = warp & 3, tid = threadIdx.x & 127, g = lane >> 2, q = lane & 3;
    const int chx = 512 + 32 * ((pair >> 3) & 1) + 8 * ((pair & 7) >> 1) + 2 * (pair >> 4) + (pair & 1);
    const bool kk2 = wg == 2 || (wg == 1 && rank == 1);
    uint32_t pz[8];
    {
      const int ch = wg == 2 ? chm + 384 : kk2 ? chx : chm + 128 * wg;
      #pragma unroll
      for (int i = 0; i < 6; i++) asm volatile("ld.global.nc.u16 %0, [%1];" : "=r"(pz[i]) : "l"(prm.ssm[i] + ch * NST + tid));
      asm volatile("ld.global.nc.u16 %0, [%1];" : "=r"(pz[6]) : "l"(prm.logdt + ch));
      asm volatile("ld.global.nc.u16 %0, [%1];" : "=r"(pz[7]) : "l"(prm.Dskip + ch));
    }
    uint32_t scal = 0;
    if (warp == 11) {
      if (elect_one()) {
        mbar_init(sb + B_X, 1);
        fence_async_smem();
        mbar_expect_tx(sb + B_X, 18432);
        #pragma unroll
        for (int s = 0; s < NSTG; s++) { mbar_init(sb + B_FULL + 8 * s, 1); mbar_init(sb + B_EMPTY + 8 * s, 4); mbar_init(sb + B_A + 8 * s, 1); mbar_init(sb + B_A + 72 + 8 * s, 1); }
        #pragma unroll
        for (int s = 0; s < 6; s++) mbar_init(sb + B_STAGED + 8 * s, 256);
        mbar_init(sb + B_CS, 1); mbar_init(sb + B_STFREE, 1); mbar_init(sb + B_IN, 1);
        mbar_init(sb + B_P1, 256); mbar_init(sb + B_U, 1); mbar_init(sb + B_MU, 8); mbar_init(sb + B_R2, 3); mbar_init(sb + B_RES, 32);
        mbar_init(sb + B_T, 1); mbar_init(sb + B_E, 1); mbar_init(sb + B_T + 8, 1); mbar_init(sb + B_HD, 12); mbar_init(sb + B_CSD, 4); mbar_init(sb + B_CSL, 1); mbar_init(sb + B_XD, 12); mbar_init(sb + B_EF, 1); mbar_init(sb + B_EF + 8, 1); mbar_init(sb + B_EF + 16, 1); mbar_init(sb + B_KD, 1); mbar_init(sb + B_KD + 8, 1);
        mbar_expect_tx(sb + B_T + 8, T_USED + 8192);
        asm volatile("fence.mbarrier_init.release.cluster;" ::: "memory");
        bulk_g2s(sb + P_XR, prm.x + (size_t)cta * 16 * DM, 18432, sb + B_X);
        STAMP(156);
      }
      __syncwarp();
    } else if (warp < 6) {
      asm volatile("cp.async.cg.shared.global [%0], [%1], 16;" :: "r"(sb + P_PZ + (lane >> 4) * 1536 + warp * 256 + (lane & 15) * 16),
                   "l"(prm.ssm[warp] + (chm + 128 + 128 * (lane >> 4)) * NST + (lane & 15) * 8) : "memory");
    } else if (warp == 6) {
      asm volatile("ld.global.nc.u16 %0, [%1];" : "=r"(scal) : "l"(((lane & 2) ? prm.Dskip : prm.logdt) + chm + 128 + 128 * (lane & 1)));
    } else if (warp == 7) {
      asm volatile("ld.relaxed.gpu.global.u32 %0, [%1];" : "=r"(scal) : "l"(prm.scr->sync + C_EP));
    } else if (warp == 8) {
      if (elect_one()) {
        #pragma unroll
        for (int i = 7; i >= 0; i--) asm volatile("prefetch.tensormap [%0];" :: "l"(&maps.hT + i) : "memory");
      }
      __syncwarp();
    } else if (warp == 9) {
      if (lane < 16) sts128(sb + SM_ONE + lane * 16, 0x3f803f80, 0x3f803f80, 0x3f803f80, 0x3f803f80);
      if ((sb & 0x3FFFF) != SMEM_BASE) __trap();
    }
    if (tid < KC_SZ / 16) sts128(sb + P_KC + wg * KC_SZ + tid * 16, 0, 0, 0, 0);
    asm volatile("barrier.cluster.arrive.relaxed.aligned;" ::: "memory");
    __syncwarp();
    const uint32_t kbuf = wg * A_HALF;
    const uint32_t kc = sb + P_KC + wg * KC_SZ + 16;
    const uint32_t ka = sb + kbuf + tid * 16;
    const uint32_t pb = sb + (wg == 2 ? P_P2 : P_P0 + wg * PP_SZ);
    const uint32_t sg0 = sb + (wg == 2 ? P_S2 : kbuf + P_S0);
    auto saddr = [&](int c) { return (c >> 3) * 128 + (((c & 7) ^ ((c >> 3) & 1)) << 4); };
    uint32_t ad[5];
    {
      const int hf = (lane >> 3) & 1, kp = (lane & 7) >> 1, sg = lane & 1, kh = lane >> 4;
      const int c = 2 * lane + wq, e0 = 8 * (wq & 1) + g - 2 * q;
      ad[0] = (tid * 128 + ((tid & 7) << 4)) | (tid * 128 + (((tid - 1) & 7) << 4)) << 16;
      ad[1] = saddr(2 * tid) | (saddr(2 * tid + 2) ^ 32) << 16;
      ad[2] = ((saddr(4 * kp + wq + 16 * hf - kh) ^ (sg << 5)) + (sg ? S_Z2 : S_Z1)) | ((saddr(4 * kp + wq + 16 * hf + 32 - 32 * kh) ^ (sg << 5)) + (sg ? S_Y2 : S_Y1)) << 16;
      ad[3] = (80 + (wq >> 1) * 80 + e0 * 4 - (e0 < 0 ? 16 : 0)) | (80 + (wq >> 1) * 80 + e0 * 4 - (e0 < 8 ? 48 : 32)) << 16;
      ad[4] = ((wq >> 1) * PW_SZ + (c ^ ((c >> 3) & 1)) * 16) | ((tid * 32) ^ ((lane & 4) << 2)) << 16;
      keepu<5>(ad);
    }
      uint32_t ua[3];
      #pragma unroll
      for (int i = 0; i < 3; i++) {
        const int Q = (warp >> 1) * 3 + i;
        const int grp = Q < 16 ? ((Q & 3) << 5 | lane) : 128 + ((Q & 1) << 3 | (lane & 7));
        const int slot = Q < 16 ? (Q >> 2) : (lane >> 3);
        ua[i] = sb + grp * 128 + (((slot * 2 + (warp & 1)) ^ (lane & 7) ^ (Q < 16 ? cta & 7 : 0)) << 4);
      }
      uint32_t xa = sb + P_XR + (g + 8 * (warp & 1)) * 1152;
      uint32_t la = sb + P_LN + (g + 8 * (warp & 1)) * 48;
      uint32_t xq = xa + (warp >> 1) * 192 + q * 16;
      keepu<3>(ua);
      asm volatile("" : "+r"(xa), "+r"(la), "+r"(xq));
    auto gen_p = [&]() {
      const float dt = bf_round(expf(bf_lo(pz[6])));
      const float zr2 = dt * bf_lo(pz[0]) * 1.4426950408889634f, zt = dt * bf_lo(pz[1]) * 0.15915494309189535f;
      const float br = dt * bf_lo(pz[2]), bi = dt * bf_lo(pz[3]), cr = bf_lo(pz[4]), ci = bf_lo(pz[5]);
      const cf E1 = cexp_n(zr2, zt, 1.f), E128 = cexp_n(zr2, zt, 128.f);
      cf a[8], b[8], c[8], d[8], e[8];
      const cf E2 = cmul(E1, E1), E256 = cmul(E128, E128), E512 = cmul(E256, E256), E1024 = cmul(E512, E512);
      a[0] = {fmaf(cr, br, -ci * bi), fmaf(cr, bi, ci * br)};
      a[1] = cmul(a[0], E1);
      #pragma unroll
      for (int i = 2; i < 8; i++) a[i] = cmul(a[i - 2], E2);
      st_chunk(ka, a);
      #pragma unroll
      for (int i = 0; i < 8; i++) b[i] = cmul(a[i], E128);
      st_chunk(ka + 4096, b);
      #pragma unroll
      for (int i = 0; i < 8; i++) c[i] = cmul(i < 4 ? a[2 * i] : b[2 * (i - 4)], E256);
      st_chunk(ka + 2 * 4096, c);
      d[0] = cmul(a[0], E512); d[1] = cmul(a[4], E512); d[2] = cmul(b[0], E512); d[3] = cmul(b[4], E512);
      d[4] = cmul(c[0], E512); d[5] = cmul(c[2], E512); d[6] = cmul(c[4], E512); d[7] = cmul(c[6], E512);
      st_chunk(ka + 3 * 4096, d);
      e[0] = cmul(a[0], E1024); e[1] = cmul(b[0], E1024); e[2] = cmul(c[0], E1024); e[3] = cmul(c[4], E1024);
      e[4] = cmul(d[0], E1024); e[5] = cmul(d[2], E1024); e[6] = cmul(d[4], E1024); e[7] = cmul(d[6], E1024);
      st_chunk(ka + 4 * 4096, e);
      const cf f = cmul(e[0], E1024);
      sts128(ka + 5 * 4096, pack_bf16(f.r, 0.f), 0, 0, 0);
      sts128(ka + 5 * 4096 + 2048, pack_bf16(f.i, 0.f), 0, 0, 0);
      {
        cf v[8];
        const cf E8 = cexp_n(zr2, -zt, 8.f), E16 = cmul(E8, E8);
        v[0] = {1.f, 0.f}; v[1] = E8; v[2] = E16;
        #pragma unroll
        for (int i = 3; i < 8; i++) v[i] = cmul(v[i - 2], E16);
        st_chunk(ka + 6 * 4096, v);
        const cf E64 = cmul(v[4], v[4]);
        v[0] = E64;
        #pragma unroll
        for (int i = 1; i < 8; i++) v[i] = cmul(v[i], E64);
        st_chunk(ka + 7 * 4096, v);
      }
    };
    float kd[8];
    auto kern_mma = [&]() {
      wg_fence();
      sfor<0, 16>([&](auto K) {
        constexpr int k = K.v;
        wgmma_ss_16<1, 1, desc_lo(k * 256, 128), (4096 >> 4), desc_lo(6 * 4096 + k * 256, 128), (4096 >> 4), (k > 0)>(kd, kbuf >> 4, kbuf >> 4);
      });
      wg_commit();
    };
    gen_p();
    if (wq == 0) STAMP(140 + wg);
    {
      if ((warp >> 1) == 3 && lane < 4) sts32(sb + P_SC + (warp & 1) * 16 + lane * 4, scal);
      asm volatile("cp.async.wait_all;" ::: "memory");
      __syncthreads();
      if (warp == 0) STAMP(59);
      mbar_wait(sb + B_X, 0);
      if (warp == 0) STAMP(60);
      epoch = lds32(sb + P_SC + 16) + 1;
      uint32_t w[12];
      #pragma unroll
      for (int i = 0; i < 3; i++) {
        const uint4 v = lds128(xq + i * 64);
        w[4 * i] = v.x; w[4 * i + 1] = v.y; w[4 * i + 2] = v.z; w[4 * i + 3] = v.w;
      }
      const uint32_t x0 = lds16(xa), nc = (x0 | x0 << 16) ^ 0x80008000u;
      float st[4] = {0.f, 0.f, 0.f, 0.f}, su[4] = {0.f, 0.f, 0.f, 0.f};
      #pragma unroll
      for (int i = 0; i < 3; i++) {
        const uint32_t a = add_bf16x2(w[4 * i], nc), b = add_bf16x2(w[4 * i + 1], nc), c = add_bf16x2(w[4 * i + 2], nc), d = add_bf16x2(w[4 * i + 3], nc);
        mma16816(st, a, 0x3f803f80u, b, 0x3f803f80u, a, b);
        mma16816(su, c, 0x3f803f80u, d, 0x3f803f80u, c, d);
      }
      const uint32_t tg = (epoch & 1) ? 0x00010001u : 0u;
      const uint32_t mu_ = g < 2 ? 0xfffefffeu : 0xffffffffu, mx = g == 1 ? 0x00010001u : 0u, t0_ = g == 0 ? tg : 0u, t1_ = g == 1 ? tg : 0u;
      #pragma unroll
      for (int i = 0; i < 3; i++)
        stsm4_t(ua[i] + P_XS, (w[4 * i] & ~mx) | t1_, (w[4 * i + 1] & ~mx) | t1_, (w[4 * i + 2] & ~mx) | t1_, (w[4 * i + 3] & ~mx) | t1_);
      if (q == (g >> 1))
        sts64(la + (warp >> 1) * 8, __float_as_uint((g & 1) ? st[3] + su[3] : st[2] + su[2]), __float_as_uint((g & 1) ? st[1] + su[1] : st[0] + su[0]));
      uint32_t cb[12];
      #pragma unroll
      for (int i = 0; i < 12; i++) cb[i] = (w[i] & mx) | t0_;
      keepu<12>(cb);
      fence_async_smem();
      __syncthreads();
      if (threadIdx.x == 96) tma2d_store(&maps.X, cta * 64, 0, sb + P_XS);
      if (warp == 0) STAMP(58);
      const float4 t0 = lds128f(la), t1 = lds128f(la + 16), t2 = lds128f(la + 32);
      const float d = ((t0.x + t0.z) + (t1.x + t1.z) + (t2.x + t2.z)) * (1.0f / DM);
      const float e2 = ((t0.y + t0.w) + (t1.y + t1.w) + (t2.y + t2.w)) * (1.0f / DM);
      const float rc = rcp_fast(ln_sd(fmaxf(fmaf(-d, d, e2), 0.f)));
      const float nmu = -bf_lo(x0) - d;
      const uint32_t nm = pack_bf16(nmu, nmu), rh = pack_bf16(rc, rc);
      const float lo = rc - bf_lo(rh);
      const uint32_t rl = pack_bf16(lo, lo);
      #pragma unroll
      for (int i = 0; i < 3; i++) {
        uint32_t a[4];
        #pragma unroll
        for (int j = 0; j < 4; j++) {
          const uint32_t dd = add_bf16x2(w[4 * i + j], nm);
          a[j] = (fma_bf16x2(dd, rh, mul_bf16x2(dd, rl)) & mu_) | cb[4 * i + j];
        }
        stsm4_t(ua[i] + P_US, a[0], a[1], a[2], a[3]);
      }
      fence_async_smem();
      if (warp == 3) {
        asm volatile("bar.sync 2, 384;" ::: "memory");
        if (lane == 0) { tma2d_store(&maps.U, cta * 64, 0, sb + P_US); bulk_commit(); }
        __syncwarp();
      } else asm volatile("bar.arrive 2, 384;" ::: "memory");
      if (warp == 0) STAMP(61);
      if (warp == 2) {
        if (elect_one()) {
          const CUtensorMap* wm = rank ? &maps.wu : &maps.wg;
          mbar_expect_tx(sb + B_CSL, pair < 16 ? 12288 : 8192);
          tma2d(sb + P_CW, wm, fs * 576, (pair >> 3) * 32, sb + B_CSL);
          tma2d(sb + P_CW + 4096, wm, fs * 576, (pair >> 3) * 32 + 256, sb + B_CSL);
          if (pair < 16) tma2d(sb + P_CW + 8192, wm, fs * 576, (pair >> 3) * 32 + 512, sb + B_CSL);
        }
        __syncwarp();
      }
      asm volatile("barrier.cluster.wait.aligned;" ::: "memory");
    }
    #pragma unroll 1
    for (int r = 0;; r++) {
      const int slot = (kk2 && r == 0) ? 5 - wg : wg;
      const uint32_t tb = sb + (slot >= 3 ? P_T3 + (slot - 3) * T_SZ : slot == 2 ? P_T2 : kbuf);
      kern_mma();
      if (warp == 3) {
        if (lane == 0) {
          bulk_wait_read();
          red_relaxed(prm.scr->sync + C_U);
        }
        __syncwarp();
        STAMP(62);
        #pragma unroll
        for (int i = 0; i < 6; i++) sts128(sb + P_US + i * 512 + lane * 16, 0, 0, 0, 0);
      }
      const int base0 = wq == 0 ? 2 * g : wq == 1 ? 512 + 2 * (g & 3) + 128 * (g >> 2) : 1024 + 486 + 32 * g;
      const int base1 = wq == 0 ? 256 + 2 * g : 768 + 230 + 2 * (g & 1) + 64 * (g >> 1);
      const int st0 = wq == 0 ? 16 : wq == 1 ? 8 : 2, st1 = wq == 0 ? 16 : 4;
      wg_wait<0>();
      keep<8>(kd);
      if (slot < 2 && tid == 0) mbar_arrive(sb + B_KD + 8 * wg);
      if (slot == 2) mbar_wait(sb + B_KD, 0);
      if (wq == 0) STAMP(101 + slot * 4);
      if (tid == 0) kd[0] += bf_lo(pz[7]);
      if (wq < 3) {
        #pragma unroll
        for (int t = 0; t < 2; t++) {
          const uint32_t w0 = pack_bf16(kd[4 * t], kd[4 * t + 1]), w1 = pack_bf16(kd[4 * t + 2], kd[4 * t + 3]);
          const int b = 8 * t + 2 * q;
          sts16(kc + base0 + st0 * b - ((t == 0 && tid == 64) ? 256 : 0), w0); sts16(kc + base0 + st0 * (b + 1), w0 >> 16);
          if (wq < 2) { sts16(kc + base1 + st1 * b - ((t == 0 && tid == 32) ? 230 : 0), w1); sts16(kc + base1 + st1 * (b + 1), w1 >> 16); }
          else if (t == 0 && lane == 0) sts16(kc + 1280 + 486, w1);
        }
      }
      bar_sync(4 + wg, 128);
      {
        const uint32_t kw = kc + 1512 + 4 * (tid < 64 ? tid - 16 : tid - 64);
        const uint32_t kg = kc + 1000 + 8 * ((tid & 63) - 16) + 4 * (tid >> 6);
        const uint32_t w0 = lds32(kw), w1 = lds32(kw - 8), w2 = lds32(kw - 16), w3 = lds32(kw - 24);
        const uint32_t b0 = lds32(kg), b1 = lds32(kg - 16), b2 = lds32(kg - 32), b3 = lds32(kg - 48);
        sts128(tb + T_B3 + tid * 16, w0, w1, w2, w3);
        sts128(tb + T_B2 + tid * 16, b0, b1, b2, b3);
      }
      if (wq == 0) {
        if (lane < 16) {
          const uint32_t dst = tb + 80 + lane * 80;
          const uint4 v0 = lds128(kc + lane * 32), v1 = lds128(kc + lane * 32 + 16);
          const uint32_t pv = lds32(kc + lane * 32 - 4);
          sts128(dst, __byte_perm(v0.x, pv, 0x7610), __byte_perm(v0.x, 0, 0x1032), __byte_perm(v0.y, v0.x, 0x7610), __byte_perm(v0.y, 0, 0x1032));
          sts128(dst + 16, __byte_perm(v0.z, v0.y, 0x7610), __byte_perm(v0.z, 0, 0x1032), __byte_perm(v0.w, v0.z, 0x7610), __byte_perm(v0.w, 0, 0x1032));
          sts128(dst + 32, __byte_perm(v1.x, v0.w, 0x7610), __byte_perm(v1.x, 0, 0x1032), __byte_perm(v1.y, v1.x, 0x7610), __byte_perm(v1.y, 0, 0x1032));
          sts128(dst + 48, __byte_perm(v1.z, v1.y, 0x7610), __byte_perm(v1.z, 0, 0x1032), __byte_perm(v1.w, v1.z, 0x7610), __byte_perm(v1.w, 0, 0x1032));
        }
      } else if (wq == 1) {
        if (lane < 16) {
          const uint32_t dst = tb + 17 * 80 + lane * 80;
          const uint4 v = lds128(kc + 512 + lane * 16);
          const uint32_t nx = lds16(kc + 512 + lane * 16 + 16), pv = lds16(kc + 512 + lane * 16 - (lane == 0 ? 2 : 0));
          sts128(dst, __byte_perm(v.x, pv, 0x5410), __byte_perm(v.x, 0, 0x1010), __byte_perm(v.x, 0, 0x1032), __byte_perm(v.y, v.x, 0x7610));
          sts128(dst + 16, __byte_perm(v.y, 0, 0x1010), __byte_perm(v.y, 0, 0x1010), __byte_perm(v.y, 0, 0x1032), __byte_perm(v.z, v.y, 0x7610));
          sts128(dst + 32, __byte_perm(v.z, 0, 0x1010), __byte_perm(v.z, 0, 0x1010), __byte_perm(v.z, 0, 0x1032), __byte_perm(v.w, v.z, 0x7610));
          sts128(dst + 48, __byte_perm(v.w, 0, 0x1010), __byte_perm(v.w, 0, 0x1010), __byte_perm(v.w, 0, 0x1032), __byte_perm(nx, v.w, 0x7610));
        }
      } else if (tid < 64 + 30) {
        const int j = tid - 64;
        const uint32_t c = lds16(kc + (j == 0 ? 768 : 1254)), cc = c | c << 16;
        sts128(j < 25 ? tb + 33 * 80 + j * 16 : tb + (j - 25) * 16, (j == 0 || j == 16) ? cc : 0u, j == 0 ? cc : j == 16 ? c << 16 : 0u, j == 0 ? cc : 0u,
               j == 0 ? c << 16 : j == 15 ? c : 0u);
      }
      fence_async_smem();
      bar_sync(4 + wg, 128);
      if (slot == 3) { if (tid == 0) mbar_arrive(sb + B_T); }
      else if (slot == 4) {
        if (wq == 0 && elect_one()) {
          uint32_t rd, rb;
          asm volatile("mapa.shared::cluster.u32 %0, %1, 0;" : "=r"(rd) : "r"(tb));
          asm volatile("mapa.shared::cluster.u32 %0, %1, 0;" : "=r"(rb) : "r"(sb + B_T + 8));
          asm volatile("cp.async.bulk.shared::cluster.shared::cta.mbarrier::complete_tx::bytes [%0], [%1], %2, [%3];" :: "r"(rd), "r"(tb), "r"(T_USED), "r"(rb) : "memory");
        }
      }
      __syncwarp();
      if (wq == 0) STAMP(102 + slot * 4);
      if (!kk2 || r) break;
      const uint32_t pa = sb + P_PZ + (wg - 1) * 1536 + tid * 2;
      #pragma unroll
      for (int i = 0; i < 6; i++) pz[i] = lds16(pa + i * 256);
      pz[6] = lds32(sb + P_SC - 4 + wg * 4); pz[7] = lds32(sb + P_SC + 4 + wg * 4);
      gen_p();
      if (wq == 0) STAMP(100 + wg * 4);
      fence_async_smem();
      bar_sync(4 + wg, 128);
    }
    if (warp == 3) {
      poll_ge_warp(prm.scr->sync + C_U, epoch * 128 - SLU);
      STAMP(63);
      if (elect_one()) {
        mbar_expect_tx(sb + B_U, 16384);
        bulk_g2s(sb + P_U0, prm.scr->U + (size_t)grpm * 8192, 16384, sb + B_U);
        mbar_expect_tx(sb + B_E, 16384);
        bulk_g2s(sb + P_X0, prm.scr->X + (size_t)grpm * 8192, 16384, sb + B_E);
      }
      __syncwarp();
    } else if (warp == 2) {
      if (elect_one()) {
        #pragma unroll 1
        for (int j = pair >> 3; j < 18; j += 8) tma2d_prefetch(rank ? &maps.wu : &maps.wg, fs * 576 + 64, j * 32);
      }
      __syncwarp();
    }
    if (wg == 0) {
      mbar_wait(sb + B_CSL, 0);
      STAMP(92);
      uint32_t b[3][8];
      #pragma unroll
      for (int j = 0; j < 3; j++) {
        const uint32_t ba = sb + P_CW + j * 4096 + lane * 128 + (((2 * wq) ^ (lane & 7)) << 4);
        ldsm4_t(ba, b[j][0], b[j][1], b[j][2], b[j][3]); ldsm4_t(ba ^ 16, b[j][4], b[j][5], b[j][6], b[j][7]);
      }
      float c[4][4];
      #pragma unroll
      for (int i = 0; i < 4; i++) {
        c[i][0] = c[i][1] = c[i][2] = c[i][3] = 0.f;
        #pragma unroll
        for (int j = 0; j < 3; j++) if (j < 2 || pair < 16) mma16816(c[i], 0x3f803f80u, 0u, 0x3f803f80u, 0u, b[j][2 * i], b[j][2 * i + 1]);
      }
      const float v0 = (g & 1) ? c[2][0] + c[3][0] : c[0][0] + c[1][0], v1 = (g & 1) ? c[2][1] + c[3][1] : c[0][1] + c[1][1];
      const uint32_t hi = (pack_bf16(v0, v1) & ~1u) | (epoch & 1), lo = (pack_bf16(v0 - bf_lo(hi), v1 - bf_hi(hi)) & ~1u) | (epoch & 1);
      const int row = (pair >> 3) * 2 + (g >> 1);
      if (g < 4) st_relaxed(prm.scr->cs + fs * 1024 + rank * 512 + row * 32 + (((2 * wq + (g & 1)) ^ (row & 7)) << 2) + q, g < 2 ? hi : lo);
      if (lane == 0) mbar_arrive(sb + B_CSD);
      STAMP(93);
    }
    __syncwarp();
    auto valid2 = [&](uint4* p, const char* base, uint32_t off, int sh) {
      int it = 0;
      #pragma unroll 1
      while (__any_sync(~0u, neq2(p[0].x, p[1].x, epoch << sh) & (1u << sh))) {
        p[0] = ld_piece((const uint4*)(base + off)); p[1] = ld_piece((const uint4*)(base + (off ^ 16)));
        STAMP(57);
        if (++it > (1 << 22)) __trap();
      }
    };
    const char* ebase = (const char*)prm.scr->U + (size_t)(128 + (pair & 15)) * 16384 + (pair >> 4) * 32;
    if (wq == 3) {
          mbar_wait2(sb + B_U, 0, sb + B_KD + 8 * (wg == 2), 0);
          sts128(lane < 2 ? pb + PW_SZ + lane * 16 : lane < 4 ? sb + P_UE - 64 + lane * 16 : sg0 + (lane == 4 ? S_Z1 - 32 : lane == 5 ? S_Z2 - 64 : S_Y2 + 32), 0, 0, 0, 0);
          if (wg == 1 && rank == 0 && elect_one()) {
            tma2d(sb + P_UE, &maps.E, (pair >> 4) * 16, (128 + (pair & 15)) * 128, sb + B_T + 8);
            tma2d(sb + P_XE, &maps.E, (pair >> 4) * 16, (144 + 128 + (pair & 15)) * 128, sb + B_T + 8);
          }
          if (wg == 2) {
            mbar_wait(sb + B_CSD, 0);
            uint32_t eb;
            asm volatile("mapa.shared::cluster.u32 %0, %1, %2;" : "=r"(eb) : "r"(sb + B_EMPTY + (lane >> 1) * 8), "r"(lane & 1));
            if (lane < 18) asm volatile("mbarrier.arrive.shared::cluster.b64 _, [%0], 2;" :: "r"(eb) : "memory");
          }
          __syncwarp();
        }
    uint32_t xb = 0;
    const int nc = kk2 ? 1 : 2;
    #pragma unroll 1
    for (int r = -1; r < nc; r++) {
      const int slot = wg + 3 * r;
      keepu<5>(ad);
      const uint32_t co = ad[0] & 0xffff;
      uint4 xv[2] = {make_uint4(0, 0, 0, 0), make_uint4(0, 0, 0, 0)};
      if (r >= 0) {
        const uint32_t to = slot >= 3 ? P_T3 + (slot - 3) * T_SZ : slot == 2 ? P_T2 : kbuf;
        const int us = slot == 4 ? 1 : slot;
        float acc[64];
        {
          uint32_t af[40], sf[32];
          const uint32_t t0 = sb + to + (ad[3] & 0xffff), t2 = sb + to + (ad[3] >> 16), a2 = sg0 + (ad[2] & 0xffff), a3 = sg0 + (ad[2] >> 16);
          #pragma unroll
          for (int i = 0; i < 10; i++) {
            const int o = (i < 8 ? 2 * (i & 3) + 16 * (i >> 2) : i == 8 ? 32 : 35) * 80;
            af[4 * i] = lds32(t0 + o); af[4 * i + 2] = lds32(t2 + o);
            if (i < 8) { af[4 * i + 1] = lds32(t0 + o + 640); af[4 * i + 3] = lds32(t2 + o + 640); }
            else { af[4 * i + 1] = blockIdx.y; af[4 * i + 3] = blockIdx.z; }
          }
          #pragma unroll
          for (int t = 0; t < 6; t++) ldsm4_t(a2 + t * 512, sf[4 * t], sf[4 * t + 1], sf[4 * t + 2], sf[4 * t + 3]);
          #pragma unroll
          for (int t = 0; t < 2; t++) ldsm4_t(a3 + t * 1024, sf[24 + 4 * t], sf[25 + 4 * t], sf[26 + 4 * t], sf[27 + 4 * t]);
          if (r == 0 && wg == 2 * rank) asm volatile("bar.sync 3, 256;" ::: "memory");
          keepu<40>(af);
          keepu<32>(sf);
          wg_fence();
          if (wq == 0) STAMP(123 + slot * 4);
          sfor<0, 10>([&](auto II) {
            constexpr int i = II.v == 0 ? 0 : II.v <= 2 ? II.v + 7 : II.v - 2, sh = i < 8 ? 2 * (i & 3) + 16 * (i >> 2) : i == 8 ? 32 : 64;
            sfor<sh / 32, 4>([&](auto TT) {
              constexpr int T = TT.v;
              wgmma_rs_32<0, (uint32_t)((int)desc_lo(P_U0, 16) + (32 * T - sh) * 8), DESC_HI_128, (i > 0)>(acc + 16 * T, af[4 * i], af[4 * i + 1], af[4 * i + 2], af[4 * i + 3], us * 2);
            });
          });
          sfor<0, 4>([&](auto NN) {
            constexpr int n0 = 32 - 16 * NN.v;
            sfor<1, 4>([&](auto TT) {
              constexpr int T = TT.v, t = (32 * T - 32 - n0) / 16;
              if constexpr (32 * T - 32 - n0 >= 0)
                wgmma_rs_32<0, desc_lo(T_B2 + (n0 + 16) * 16, 1024), (128 >> 4), 1>(acc + 16 * T, sf[4 * t], sf[4 * t + 1], sf[4 * t + 2], sf[4 * t + 3], to >> 4);
            });
          });
          wgmma_rs_32<0, desc_lo(T_B3, 1024), (128 >> 4), 1>(acc + 32, sf[24], sf[25], sf[26], sf[27], to >> 4);
          wgmma_rs_32<0, desc_lo(T_B3, 1024), (128 >> 4), 1>(acc + 48, sf[28], sf[29], sf[30], sf[31], to >> 4);
          wgmma_rs_32<0, desc_lo(T_B3 + 512, 1024), (128 >> 4), 1>(acc + 48, sf[24], sf[25], sf[26], sf[27], to >> 4);
          wg_commit();
        }
        if (r == 0 && wg == 1) asm volatile("bar.arrive 3, 256;" ::: "memory");
        if (warp == 11) {
          #pragma unroll 1
          for (int s = 0; s < NSTG; s++) {
            mbar_wait(sb + B_EMPTY + 8 * s, 0);
            if (elect_one()) {
              mbar_expect_tx(sb + B_FULL + 8 * s, STG);
              tma2d_mc(sb + SM_RING + rank * 4096 + s * STG, &maps.wg + rank, fs * 576, s * 32, sb + B_FULL + 8 * s, 3);
            }
          }
        }
        if (r == 0) mbar_wait2(sb + B_E, 0, sb + (kk2 ? B_E : B_T + 8 * wg), 0);
        {
          const uint32_t xa = slot < 4 ? sb + P_X0 + (co ^ (us << 5)) : sb + P_XE + ((co >> 7) << 5);
          xv[0] = lds128(xa); xv[1] = lds128(xa ^ 16);
        }
        wg_wait<0>();
        keep<64>(acc);
        if (wq == 0) STAMP(121 + slot * 4);
        if (r == 0 && co == 0) mbar_arrive(sb + B_EF + 8 * wg);
        #pragma unroll
        for (int v = 0; v < 4; v++) {
          uint32_t p[4];
          #pragma unroll
          for (int i = 0; i < 4; i++) {
            const int n = 4 * (4 * v + i);
            p[i] = n ? pack_bf16(acc[n] + acc[n - 2], acc[n + 1] + acc[n - 1]) : pack_bf16(acc[0], acc[1]);
          }
          stsm4_t(pb + (ad[4] & 0xffff) + v * 1024, p[0], p[1], p[2], p[3]);
        }
        valid2(xv, (slot < 4 ? (const char*)prm.scr->U + (size_t)grpm * 16384 : ebase) + sizeof(Scratch::U), slot < 4 ? co ^ (us << 5) : co & ~127u, 16);
        if (r == nc - 1 && lane == 0) mbar_arrive(sb + B_XD);
        xv[0].x = (xv[0].x & ~0x10000u) | ((xb & 1) << 16); xv[1].x = (xv[1].x & ~0x10000u) | ((xb & 0x100) << 8);
      } else {
        mbar_wait2(sb + B_U, 0, sb + B_KD + 8 * (wg == 2), 0);
      }
      if (r >= 0) bar_sync(4 + wg, 128);
      if (r >= 0) {
      if (wq == 0) STAMP(144 + slot);
      #pragma unroll
      for (int i = 0; i < 2; i++) {
        const uint32_t pa = pb + ((ad[4] >> 16) ^ (16 * i));
        const uint4 p0 = lds128(pa), p1 = lds128(pa + PW_SZ);
        xv[i].x = add_bf16x2(xv[i].x, add_bf16x2(p0.x, p1.x)); xv[i].y = add_bf16x2(xv[i].y, add_bf16x2(p0.y, p1.y));
        xv[i].z = add_bf16x2(xv[i].z, add_bf16x2(p0.z, p1.z)); xv[i].w = add_bf16x2(xv[i].w, add_bf16x2(p0.w, p1.w));
      }
      {
        const int ch = slot < 4 ? chm + 128 * slot : chx;
        const uint32_t b0 = __ballot_sync(~0u, xv[0].x & 1), b1 = __ballot_sync(~0u, xv[1].x & 1);
        const bool odd = co & 128;
        uint4 t = odd ? xv[0] : xv[1];
        t.x = __shfl_xor_sync(~0u, t.x, 1); t.y = __shfl_xor_sync(~0u, t.y, 1); t.z = __shfl_xor_sync(~0u, t.z, 1); t.w = __shfl_xor_sync(~0u, t.w, 1);
        const uint4 o0 = odd ? t : xv[0], o1 = odd ? xv[1] : t;
        uint4* hp = (uint4*)(prm.scr->hT + (size_t)ch * HP) + 2 * (co >> 7) - odd;
        st_piece(hp, (o0.x & ~1u) | (epoch & 1), o0.y, o0.z, o0.w);
        st_piece(hp + 2, (o1.x & ~1u) | (epoch & 1), o1.y, o1.z, o1.w);
        if (wq == 3) {
          asm volatile("bar.sync %0, 128;" :: "r"(8 + wg) : "memory");
          if (elect_one()) red_relaxed(prm.scr->sync + C_H + 32 * (r ? 2 : kk2 ? 1 : 0));
        } else asm volatile("bar.arrive %0, 128;" :: "r"(8 + wg) : "memory");
        if (elect_one()) prm.scr->hbit[ch * 4 + wq] = make_uint2(b0, b1);
        __syncwarp();
      }
      if (wq == 0) STAMP(122 + slot * 4);
      }
      if (r + 1 < nc) {
        const bool ex = slot == 1;
        const uint32_t un = (slot + 3) << 5;
        const uint32_t uc = ex ? sb + P_UE + ((co >> 7) << 5) : sb + P_U0 + (co ^ un), um = ex ? uc - 32 : sb + P_U0 - 128 + ((ad[0] >> 16) ^ un);
        if (wq == 0) STAMP(153 + slot);
        #pragma unroll 1
        while (true) {
          uint4 up[2] = {lds128(uc), lds128(uc ^ 16)};
          if (wq < 3) {
            const uint2 a = lds64(um + 8); const uint4 b = lds128(um ^ 16);
            const uint32_t z = sg0 + (ad[1] & 0xffff);
            const uint32_t w[13] = {a.x, a.y, b.x, b.y, b.z, b.w, up[0].x, up[0].y, up[0].z, up[0].w, up[1].x, up[1].y, up[1].z};
            uint32_t v[12], d[12], s4[10], s5[10], s3[11];
            #pragma unroll
            for (int j = 0; j < 12; j++) { v[j] = __byte_perm(w[j], w[j + 1], 0x5432); d[j] = add_bf16x2(w[j], v[j]); }
            #pragma unroll
            for (int j = 0; j < 11; j++) s3[j] = add_bf16x2(v[j], d[j + 1]);
            #pragma unroll
            for (int j = 0; j < 10; j++) s4[j] = add_bf16x2(d[j], d[j + 1]);
            #pragma unroll
            for (int j = 1; j < 10; j++) s5[j] = add_bf16x2(s4[j], w[j + 2]);
            sts128(z + S_Z1, s3[3], s3[4], s3[5], s3[6]);
            sts128((z ^ 16) + S_Z1, s3[7], s3[8], s3[9], s3[10]);
            sts128((z ^ 32) + S_Z2, s5[1], s5[2], s5[3], s5[4]);
            sts128((z ^ 48) + S_Z2, s5[5], s5[6], s5[7], s5[8]);
            if (wq < 2) {
              #pragma unroll
              for (int j = 0; j < 8; j++) { s3[j] = add_bf16x2(s3[j], s4[j + 2]); s4[j] = add_bf16x2(s4[j], s5[j + 2]); }
              sts128(z + S_Y1, s3[0], s3[1], s3[2], s3[3]);
              sts128((z ^ 16) + S_Y1, s3[4], s3[5], s3[6], s3[7]);
              sts128((z ^ 48) + S_Y2, s4[0], s4[1], s4[2], s4[3]);
              sts128(sg0 + S_Y2 + (ad[1] >> 16), s4[4], s4[5], s4[6], s4[7]);
            }
          }
          if (ex) {
            sts128(sb + P_U0 + (co ^ 32), up[0].x, up[0].y, up[0].z, up[0].w);
            sts128(sb + P_U0 + (co ^ 48), up[1].x, up[1].y, up[1].z, up[1].w);
            fence_async_smem();
          }
          xb = __byte_perm(up[0].x, up[1].x, 0x0062);
          if (!__any_sync(~0u, bar_or(4 + wg, neq2(up[0].x, up[1].x, epoch) & 1))) break;
          valid2(up, ex ? ebase : (const char*)prm.scr->U + (size_t)grpm * 16384, ex ? co & ~127u : co ^ un, 0);
          sts128(uc, up[0].x, up[0].y, up[0].z, up[0].w); sts128(uc ^ 16, up[1].x, up[1].y, up[1].z, up[1].w);
          fence_async_smem();
          bar_sync(4 + wg, 128);
        }
        if (wq == 0) STAMP(132 + slot * 4);
      }
      __syncwarp();
    }
    if (lane == 0) mbar_arrive(sb + B_HD);
    if (wg == 2) bar_sync(6, 128);
    __syncwarp();
    __syncwarp();
  }

  epoch = __shfl_sync(~0u, lds32(sb + P_SC + 16), 0) + 1;
  asm volatile("mov.u32 %0, %%laneid;" : "=r"(lane));
  { int t; asm volatile("mov.u32 %0, %%tid.x;" : "=r"(t)); warp = __shfl_sync(~0u, t >> 5, 0); }
  if (warp >= 8) {
    reg_dec<24>();
    if (warp == 8) {
      const CUtensorMap* wmap = rank ? &maps.wu : &maps.wg;
      const uint32_t dst0 = sb + SM_RING + rank * 4096;
      const int f0 = fs * 576;
      uint32_t ph = 1;
      #pragma unroll 1
      for (int it = 1; it < 27; it++) {
        int x, y0, dy;
        if (it < 18) { x = f0 + (it >> 1) * 64; y0 = (it & 1) * 288; dy = 32; }
        else { x = (it == 18 ? 8 : ((fs + it - 18) & 7)) * 64; y0 = f0 + rank * 32; dy = 64; wmap = &maps.wd; }
        if (it < 15 && elect_one()) {
          const int xn = f0 + ((it + 3) >> 1) * 64, yn = ((it + 3) & 1) * 288 + (pair >> 3) * 32;
          tma2d_prefetch(wmap, xn, yn);
          if (pair < 8) tma2d_prefetch(wmap, xn, yn + 256);
          if (it < 10) l2_prefetch(prm.Wd + (size_t)(f0 + mt * 36 + (it - 1) * 4) * DM, 4608);
        }
        #pragma unroll
        for (int s = 0; s < NSTG; s++) {
          mbar_wait(sb + B_EMPTY + 8 * s, ph);
          if (elect_one()) {
            mbar_expect_tx(sb + B_FULL + 8 * s, STG);
            tma2d_mc(dst0 + s * STG, wmap, x, y0 + s * dy, sb + B_FULL + 8 * s, 3);
          }
        }
        ph ^= 1;
      }
    } else {
      if (warp != 10) {
        const int hf = warp == 11;
        poll_ge_warp(prm.scr->sync + C_H, epoch * 192);
        mbar_wait(sb + B_EF + 8 * hf, 0);
        if (elect_one()) {
          #pragma unroll
          for (int s = 0; s < 3; s++) {
            mbar_expect_tx(sb + B_A + 72 * hf + 8 * s, 8192);
            tma2d(sb + SM_A + hf * A_HALF + s * 8192, &maps.hT, mt * 128 + hf * 64, s * 64, sb + B_A + 72 * hf + 8 * s);
          }
        }
        __syncwarp();
        STAMP(48 + hf);
      }
      if (warp == 9) {
        #pragma unroll 1
        for (int w = 1; w < 3; w++) {
          const unsigned* cp = prm.scr->sync + C_H + 32 * w;
          unsigned va = ld_relaxed(cp);
          __nanosleep(150);
          #pragma unroll 1
          for (int it = 0;; it++) {
            const unsigned vb = ld_relaxed(cp);
            if (__all_sync(~0u, (int)(va - (epoch * 192 - SLK)) >= 0)) break;
            va = ld_relaxed(cp);
            if (__all_sync(~0u, (int)(vb - (epoch * 192 - SLK)) >= 0)) break;
            if (it > (1 << 21)) __trap();
          }
          STAMP(96 + w);
          mbar_wait(sb + (w == 1 ? B_XD : B_HD), 0);
          if (elect_one()) {
            #pragma unroll
            for (int i = 0; i < 3; i++) {
              const int s = 3 * w + i;
              if (i && w == 2) mbar_wait(sb + B_FULL + 8 * (2 * i - 2 + PCE), 1);
              mbar_expect_tx(sb + B_A + 8 * s, 8192);
              tma2d(sb + SM_A + s * 8192, &maps.hT, mt * 128, s * 64, sb + B_A + 8 * s);
              mbar_expect_tx(sb + B_A + 72 + 8 * s, 8192);
              tma2d(sb + SM_A + A_HALF + s * 8192, &maps.hT, mt * 128 + 64, s * 64, sb + B_A + 72 + 8 * s);
            }
          }
          __syncwarp();
          STAMP(50 + 3 * w);
        }
      } else if (warp == 10) {
        mbar_wait2(sb + B_EF, 0, sb + B_EF + 8, 0);
        const uint32_t tT = (epoch & 1) ? 0xffffffffu : 0u;
        #pragma unroll 1
        for (int it = 1;; it++) {
          if (elect_one()) {
            mbar_expect_tx(sb + B_CSL, 4096);
            bulk_g2s(sb + SM_CS, prm.scr->cs + fs * 1024, 4096, sb + B_CSL);
          }
          mbar_wait(sb + B_CSL, it & 1);
          uint32_t bad = 0;
          #pragma unroll 2
          for (int i = 0; i < 8; i++) {
            const uint4 v = lds128(sb + SM_CS + i * 512 + lane * 16);
            bad |= neq2(v.x, v.y, tT) | neq2(v.z, v.w, tT);
          }
          if (!__any_sync(~0u, bad & 1)) break;
          if (it > (1 << 20)) __trap();
        }
        if (lane == 0) mbar_arrive(sb + B_CS);
        STAMP(99);
      } else {
        mbar_wait(sb + B_HD, 0);
      }
      mbar_wait(sb + B_MU, 0);
      #pragma unroll 1
      for (int tg = warp == 11 ? 8 : warp - 9; tg < 8; tg += 2) {
        const uint32_t ma = sb + SM_MU + (tg * 16 + (lane >> 2)) * 4;
        uint32_t la = sb + SM_A + (tg >> 2) * A_HALF + (((lane >> 4) * 8 + (lane & 7)) * 128) + (((2 * (tg & 3) + ((lane >> 3) & 1)) ^ (lane & 7)) * 16);
        float q0 = 0.f, q1 = 0.f;
        #pragma unroll 1
        for (int k = 0; k < 36; k++, la += 2048) {
          uint32_t a, b, c, d;
          ldsm4_t(la, a, b, c, d);
          float v;
          v = bf_lo(a); q0 = fmaf(v, v, q0); v = bf_lo(b); q1 = fmaf(v, v, q1);
          v = bf_hi(a); q0 = fmaf(v, v, q0); v = bf_hi(b); q1 = fmaf(v, v, q1);
          v = bf_lo(c); q0 = fmaf(v, v, q0); v = bf_lo(d); q1 = fmaf(v, v, q1);
          v = bf_hi(c); q0 = fmaf(v, v, q0); v = bf_hi(d); q1 = fmaf(v, v, q1);
        }
        q0 += __shfl_xor_sync(~0u, q0, 1); q1 += __shfl_xor_sync(~0u, q1, 1);
        q0 += __shfl_xor_sync(~0u, q0, 2); q1 += __shfl_xor_sync(~0u, q1, 2);
        const float dm = __uint_as_float(lds32(ma + (lane & 1) * 32));
        const float sd = ln_sd(fmaxf(fmaf(-dm, dm, ((lane & 1) ? q1 : q0) * (1.0f / DM)), 0.f));
        if ((lane & 2) == 0) sts32(ma + (SM_R2 - SM_MU) + (lane & 1) * 32, __float_as_uint(rcp_fast(sd * sd)));
      }
      __syncwarp();
      if (lane == 0) mbar_arrive(sb + B_R2);
      if (warp == 9) STAMP(47);
      if (warp == 11) {
        uint4* dst = prm.scr->part + (size_t)((mt * 9 + fs) * 3) * 1024 + lane;
        #pragma unroll 1
        for (int i = 0; i < 100; i++) {
          if (i == 96) dst = prm.scr->part + (size_t)((mt * 9 + 8) * 3) * 1024 + fs * 128 + lane;
          *dst = make_uint4(0, 0, 0, 0);
          dst += 32;
          __nanosleep(ZSL);
        }
        __syncwarp();
        if (elect_one()) {
          red_add(prm.scr->sync + C_Z + 32 * mt, 1);
          red_relaxed(prm.scr->sync + C_R);
          STAMP(46);
        }
      }
      __syncwarp();
      mbar_wait(sb + B_R2, 0);
      if (warp != 10) {
        const uint32_t par = warp == 11;
        if (elect_one()) {
          if (par) {
            poll_ge(prm.scr->sync + C_Z + 32 * mt, epoch * 8);
            mbar_arrive(sb + B_STFREE);
          }
          #pragma unroll 1
          for (int st = par; st < 6; st += 2) {
            mbar_wait(sb + B_STAGED + 8 * st, 0);
            STAMP(74 + st);
            red_add(prm.scr->cnt + (mt * 9 + (st == 0 ? 8 : ((fs + st) & 7))) * 8, 1);
            STAMP(84 + st);
          }
          if (!par) {
            mbar_expect_tx(sb + B_IN, 16384);
            poll_ge(prm.scr->cnt + (mt * 9 + fs) * 8, epoch * 5);
            const char* src = (const char*)prm.scr->part + (size_t)((mt * 9 + fs) * 3) * 16384;
            bulk_g2s(sb + SM_A + ((fs + 2) & 7) * 8192, src, 8192, sb + B_IN);
            bulk_g2s(sb + SM_A + A_HALF + ((fs + 2) & 7) * 8192, src + 8192, 8192, sb + B_IN);
            STAMP(44);
          }
        }
      } else {
        mbar_wait(sb + B_P1, 0);
        if (elect_one()) {
          poll_ge(prm.scr->sync + C_R, epoch * 128);
          if (cta == 0) st_relaxed(prm.scr->sync + C_EP, epoch);
          mbar_expect_tx(sb + B_X, 3 * 8192);
          tma2d(sb + SM_A + (fs >> 2) * A_HALF + 8 * 8192, &maps.hT, mt * 128 + (fs >> 2) * 64, 512, sb + B_X);
          tma2d(sb + SM_A + fs * 8192, &maps.hT, mt * 128, fs * 64, sb + B_X);
          tma2d(sb + SM_A + A_HALF + fs * 8192, &maps.hT, mt * 128 + 64, fs * 64, sb + B_X);
        }
        __syncwarp();
        mbar_wait(sb + B_X, 1);
        #pragma unroll 1
        for (int i = 0; i < 4; i++) {
          const int ch = (i < 2 ? fs : 8) * 64 + (i & 1) * 32 + lane;
          const uint2 bt = __ldcg(prm.scr->hbit + ch * 4 + (mt >> 2));
          const uint32_t fl = (epoch & 1) ? 0xffu : 0u;
          uint32_t m = (((bt.x >> ((mt & 3) * 8)) ^ fl) & 0xff) | ((((bt.y >> ((mt & 3) * 8)) ^ fl) & 0xff) << 8);
          if (i >= 2) m &= 0x101u << fs;
          const uint32_t ra = sb + SM_A + ch * 128;
          #pragma unroll 4
          for (int j = 0; j < 16; j++)
            if ((m >> j) & 1) asm volatile("red.shared.xor.b32 [%0], 1;" :: "r"(ra + ((j >> 2) & 1) * A_HALF + ((((j & 3) * 2 + (j >> 3)) ^ (lane & 7)) << 4)) : "memory");
        }
        mbar_arrive(sb + B_RES);
        poll_ge(prm.scr->cnt + (mt * 9 + 8) * 8, epoch * 8);
        mbar_wait(sb + B_RES, 0);
        #pragma unroll 1
        for (int i = 0; i < 8; i++) {
          const int row = fs * 16 + (lane >> 2) + (i & 1) * 8;
          const uint32_t* pp = (const uint32_t*)(prm.scr->part + (size_t)((mt * 9 + 8) * 3) * 1024 + fs * 128 + (i >> 1) * 32 + lane) + (i & 1);
          const uint32_t v0 = __ldcg(pp), v1 = __ldcg(pp + 2);
          uint32_t a, c;
          asm volatile("ldmatrix.sync.aligned.m8n8.x2.trans.shared.b16 {%0, %1}, [%2];" : "=r"(a), "=r"(c)
                       : "r"(sb + SM_A + (fs >> 2) * A_HALF + 8 * 8192 + (i >> 1) * 2048 + (lane & 15) * 128 + (((2 * (fs & 3) + (i & 1)) ^ (lane & 7)) * 16)) : "memory");
          const float e = __uint_as_float(lds32(sb + SM_R2 + row * 4));
          uint32_t* op = (uint32_t*)out + (mt * 128 + row) * (DM / 2) + 256 + (i >> 1) * 8 + (lane & 3);
          op[0] = pack_bf16(fmaf(bf_lo(v0), e, bf_lo(a)), fmaf(bf_hi(v0), e, bf_hi(a)));
          op[4] = pack_bf16(fmaf(bf_lo(v1), e, bf_lo(c)), fmaf(bf_hi(v1), e, bf_hi(c)));
        }
        STAMP(45);
      }
    }
    PROF_DUMP();
  } else {
    reg_inc<240>();
    const int wg = warp >> 2, wq = warp & 3;
    const uint32_t abase = sb + SM_A + wg * A_HALF;
    uint32_t ebar;
    asm volatile("mapa.shared::cluster.u32 %0, %1, %2;" : "=r"(ebar) : "r"(sb + B_EMPTY), "r"(lane & 1));
    const bool arr = wq == 0 && lane < 2;
    const uint32_t lm_addr = abase + (((lane >> 4) * 8 + (lane & 7)) * 128) + (((2 * wq + ((lane >> 3) & 1)) ^ (lane & 7)) * 16);
    uint32_t h[144];
    float acc[64];
    uint32_t gq[16], uq[16];
    if (wq == 0) STAMP(wg * 24 + 1);
    if (warp == 0) GST32(39);
    uint32_t d[9][16];
    auto rs_chunk = [&](auto FIRST, float* sa, uint32_t m0, uint32_t m1) {
      constexpr bool first = FIRST.v;
      auto fetch = [&](uint32_t* dd, uint32_t a) {
        #pragma unroll
        for (int i = 0; i < 4; i++) ldsm4_t(a + i * 2048, dd[4 * i], dd[4 * i + 1], dd[4 * i + 2], dd[4 * i + 3]);
      };
      auto centre = [&](uint32_t* dd, uint32_t a) {
        #pragma unroll
        for (int i = 0; i < 16; i++) dd[i] = add_bf16x2(dd[i], (i & 1) ? m1 : m0);
        #pragma unroll
        for (int i = 0; i < 4; i++) stsm4_t(a + i * 2048, dd[4 * i], dd[4 * i + 1], dd[4 * i + 2], dd[4 * i + 3]);
      };
      const uint32_t tT = (epoch & 1) ? 0xffffffffu : 0u, tM = lane < 4 ? 0x00010001u : 0u;
      uint32_t e[9][4];
      auto stale = [&](const uint32_t* dd) {
        uint32_t t[8];
        #pragma unroll
        for (int i = 0; i < 8; i++) t[i] = neq2(dd[2 * i], dd[2 * i + 1], tT);
        return __any_sync(~0u, ((t[0] | t[1] | t[2]) | (t[3] | t[4] | t[5]) | (t[6] | t[7])) & tM);
      };
      auto check = [&](uint32_t* dd, uint32_t* ee, int j) {
        if (__builtin_expect(stale(dd), 0)) {
          #pragma unroll 1
          for (int i = 0; i < 4; i++) {
            const int row = j * 64 + (i >> 1) * 32 + lane;
            const uint4* src = (const uint4*)(prm.scr->hT + (size_t)row * HP + mt * 128 + warp * 16) + (i & 1);
            uint4 p;
            int it = 0;
            p = ld_piece(src);
            #pragma unroll 1
            while (__any_sync(~0u, (p.x ^ epoch) & 1)) { p = ld_piece(src); if (++it > (1 << 22)) __trap(); }
            sts128(abase + row * 128 + (((2 * wq + (i & 1)) ^ (lane & 7)) << 4), p.x, p.y, p.z, p.w);
          }
          __syncwarp();
          fetch(dd, lm_addr + j * 8192);
          STAMP(43);
        }
        #pragma unroll
        for (int i = 0; i < 4; i++) ee[i] = add_bf16x2(add_bf16x2(dd[i], dd[4 + i]), add_bf16x2(dd[8 + i], dd[12 + i]));
      };
      if (first) mbar_wait2(sb + B_A + 72 * wg, 0, sb + B_A + 72 * wg + 8, 0);
      if (first) { fetch(d[0], lm_addr); fetch(d[1], lm_addr + 8192); }
      mbar_wait2(sb + B_FULL, 0, sb + B_FULL + 8, 0);
      if (first) check(d[0], e[0], 0); else centre(d[0], lm_addr);
      sfor<0, 9>([&](auto J) {
        constexpr int j = J.v, s0 = (2 * j) % NSTG, s1 = (2 * j + 1) % NSTG;
        keepu<16>(d[j]);
        if (first) keepu<4>(e[j]);
        wg_fence();
        if (first) {
          wgmma_rs_8<0, desc_lo(SM_ONE, 0), 0, (j > 0)>(sa, e[j][0], e[j][1], e[j][2], e[j][3], 0);
          if (j == 8) wg_commit();
        }
        sfor<0, 4>([&](auto K) {
          constexpr int k = K.v;
          wgmma_rs_128<1, desc_lo(SM_RING + (k < 2 ? s0 : s1) * STG + (k & 1) * 2048, 4096), DESC_HI_128, (j + k > 0)>(acc, d[j][4 * k], d[j][4 * k + 1], d[j][4 * k + 2], d[j][4 * k + 3], 0);
          if (!first && j == 8 && k == 2) wg_commit();
        });
        wg_commit();
        if (!first && j == 0 && wg == 0) asm volatile("bar.arrive 1, 256;" ::: "memory");
        if (j < 8) { if (first) check(d[j < 8 ? j + 1 : 0], e[j < 8 ? j + 1 : 0], j + 1); else centre(d[j < 8 ? j + 1 : 0], lm_addr + (j + 1) * 8192); }
        if (j > 0) {
          wg_wait<1>();
          if (arr) { mbar_arrive_cl(ebar + 8 * ((2 * j + NSTG - 2) % NSTG)); mbar_arrive_cl(ebar + 8 * ((2 * j + NSTG - 1) % NSTG)); }
        }
        if (first && j < 7) mbar_wait3(sb + B_A + 72 * wg + 8 * (j + 2), 0, sb + B_FULL + 8 * ((2 * j + 2) % NSTG), (2 * j + 2) / NSTG, sb + B_FULL + 8 * ((2 * j + 3) % NSTG), (2 * j + 3) / NSTG);
        else if (first && j == 7) mbar_wait3(sb + B_CS, 0, sb + B_FULL + 8 * ((2 * j + 2) % NSTG), (2 * j + 2) / NSTG, sb + B_FULL + 8 * ((2 * j + 3) % NSTG), (2 * j + 3) / NSTG);
        else if (j < 8) mbar_wait2(sb + B_FULL + 8 * ((2 * j + 2) % NSTG), (2 * j + 2) / NSTG, sb + B_FULL + 8 * ((2 * j + 3) % NSTG), (2 * j + 3) / NSTG);
        if (j < 7 && (first || j + 2 >= KEEP)) fetch(d[j < 7 ? j + 2 : 0], lm_addr + (j + 2) * 8192);
        if (first && warp == 0) STAMP(j < 6 ? 14 + j : 34 + j);
      });
    };
    {
      float sa[4];
      rs_chunk(IC<1>{}, sa, 0, 0);
      keep<4>(sa);
      const float mu0 = sa[0] * (1.0f / DM), mu1 = sa[2] * (1.0f / DM);
      const uint32_t m0 = pack_bf16(-mu0, -mu0), m1 = pack_bf16(-mu1, -mu1);
      uint32_t ca[4] = {m0, m1, m0 ^ blockIdx.y, m1 ^ blockIdx.y};
      keepu<4>(ca);
      wg_fence();
      wgmma_rs_128<1, desc_lo(SM_CS, 2048), DESC_HI_128, 1>(acc, ca[0], ca[1], ca[2], ca[3], 0);
      wg_commit();
      if ((lane & 2) == 0) sts32(sb + SM_MU + (warp * 16 + (lane >> 2) + (lane & 1) * 8) * 4, __float_as_uint((lane & 1) ? mu1 + bf_lo(m1) : mu0 + bf_lo(m0)));
      wg_wait<0>();
      keep<64>(acc);
      if (arr) { mbar_arrive_cl(ebar + 8 * (NSTG - 1)); if (WD == 2) mbar_arrive_cl(ebar + 8 * (NSTG - 2)); }
      #pragma unroll
      for (int v = 0; v < 16; v++) h[v] = mul_bf16x2(pack_bf16_relu(acc[2 * v], acc[2 * v + 1]), pack_bf16(acc[32 + 2 * v], acc[32 + 2 * v + 1]));
      if (wq == 0) STAMP(wg * 24 + 2);
      if (warp == 0) GST32(90);
      if (wg == 1) asm volatile("bar.sync 1, 256;" ::: "memory");
      rs_chunk(IC<0>{}, sa, m0, m1);
      fence_async_smem();
      bar_sync(4 + wg, 128);
      if (lane == 0) mbar_arrive(sb + B_MU);
      #pragma unroll
      for (int i = 16; i < 128; i++) h[i] = 0;
      keepu<128>(h);
    }
    auto finish = [&]() {
      wg_wait<0>();
      keep<64>(acc);
      if (arr) { mbar_arrive_cl(ebar + 8 * (NSTG - 1)); mbar_arrive_cl(ebar + 8 * (NSTG - 2)); }
      #pragma unroll
      for (int v = 0; v < 16; v++) {
        gq[v] = pack_bf16_relu(acc[2 * v], acc[2 * v + 1]);
        uq[v] = pack_bf16(acc[32 + 2 * v], acc[32 + 2 * v + 1]);
      }
    };
    finish();
    #pragma unroll 1
    for (int c = 1; c < 8; c++) {
      if (wq == 0) STAMP(wg * 24 + 2 + c);
      if (LAG > 0 && wg == 1) asm volatile("bar.sync 1, 256;" ::: "memory");
      #pragma unroll 1
      for (int half = 0; half < 2; half++) {
        const uint32_t alo = wg * (A_HALF >> 4) + half * ((9 * 4096) >> 4);
        sfor<0, NSTG>([&](auto S) {
          constexpr int s = S.v;
          mbar_wait(sb + B_FULL + 8 * s, half);
          wg_fence();
          if (s == 0) wgmma_ssp_128<1, 1, desc_lo(SM_A, 4096), DESC_HI_128, desc_lo(SM_RING, 4096), DESC_HI_128>(acc, alo, 0, half);
          else wgmma_ss_128<1, 1, desc_lo(SM_A + s * 4096, 4096), DESC_HI_128, desc_lo(SM_RING + s * STG, 4096), DESC_HI_128, 1>(acc, alo, 0);
          wgmma_ss_128<1, 1, desc_lo(SM_A + s * 4096 + 2048, 4096), DESC_HI_128, desc_lo(SM_RING + s * STG + 2048, 4096), DESC_HI_128, 1>(acc, alo, 0);
          wg_commit();
          if (s == LAG - 1 && wg == 0 && half == 0) asm volatile("bar.arrive 1, 256;" ::: "memory");
          if (s == NSTG - 1 && half == 0) place_h(h, gq, uq, c);
          wg_wait<WD>();
          if (arr && (s >= WD || half > 0)) mbar_arrive_cl(ebar + 8 * ((s + NSTG - WD) % NSTG));
        });
      }
      finish();
    }
    #pragma unroll
    for (int i = 0; i < 16; i++) h[128 + i] = mul_bf16x2(gq[i], uq[i]);
    if (wq == 0) STAMP(wg * 24 + 10);
    if (warp == 0) GST32(91);
    mbar_arrive(sb + B_P1);
    float accA[32], accB[32];
    #pragma unroll
    for (int i = 0; i < 32; i++) accB[i] = 0.f;
    uint32_t toff = wq * 2048 + lane * 16;
    asm volatile("" : "+r"(toff));
    #pragma unroll 1
    for (int st = 0;; st += 2) {
      if (st == 8 && wq == 0) STAMP(wg * 24 + 11);
      if (warp == 0) STAMP(64 + st);
      p2_step<true, 0, CUT, false>(sb, ebar, arr, st, h, accA, accB, toff, wg, fs, mt, prm.scr->part);
      if (st == 8) break;
      p2_step<true, CUT, NSTG, false>(sb, ebar, arr, st, h, accA, accB, toff, wg, fs, mt, prm.scr->part);
      if (warp == 0) STAMP(65 + st);
      p2_step<false, 0, NSTG, false>(sb, ebar, arr, st + 1, h, accB, accA, toff, wg, fs, mt, prm.scr->part);
    }
    if (warp == 0) STAMP(20);
    int lane2; asm volatile("mov.u32 %0, %%laneid;" : "=r"(lane2));
#define lane lane2
    const char* in6 = (const char*)prm.scr->part + (size_t)(((mt * 9 + fs) * 3 + 1) * 2 + wg) * 8192;
    const char* in7 = in6 + 16384;
    uint4 p6[4], p7[4];
    ld_pieces<512>(p6, in6, toff);
    p2_step<true, CUT, NSTG - 1, true>(sb, ebar, arr, 8, h, accA, accB, toff, wg, fs, mt, prm.scr->part);
    ld_pieces<512>(p7, in7, toff);
    p2_step<true, NSTG - 1, NSTG, true>(sb, ebar, arr, 8, h, accA, accB, toff, wg, fs, mt, prm.scr->part);
    const uint32_t lm2 = abase + (((lane >> 4) * 8 + (lane & 7)) * 128) + (((2 * wq + ((lane >> 3) & 1)) ^ (lane & 7)) * 16);
    const uint32_t ra = sb + SM_R2 + (warp * 16 + (lane >> 2)) * 4;
    const float r0 = __uint_as_float(lds32(ra)), r1 = __uint_as_float(lds32(ra + 32));
    mbar_wait2(sb + B_RES, 0, sb + B_IN, 0);
    if (warp == 0) STAMP(21);
    uint4 sm[4];
    #pragma unroll
    for (int i = 0; i < 4; i++) sm[i] = lds128(abase + ((fs + 2) & 7) * 8192 + toff + i * 512);
    fix_pieces<512>(p6, in6, toff);
    if (warp == 0) STAMP(24);
    uint32_t hr[16];
    #pragma unroll
    for (int i = 0; i < 4; i++) {
      sm[i] = make_uint4(add_bf16x2(sm[i].x, p6[i].x), add_bf16x2(sm[i].y, p6[i].y), add_bf16x2(sm[i].z, p6[i].z), add_bf16x2(sm[i].w, p6[i].w));
      asm volatile("" : "+r"(sm[i].x), "+r"(sm[i].y), "+r"(sm[i].z), "+r"(sm[i].w));
      ldsm4_t(lm2 + fs * 8192 + i * 2048, hr[4 * i], hr[4 * i + 1], hr[4 * i + 2], hr[4 * i + 3]);
    }
    fix_pieces<512>(p7, in7, toff);
    if (warp == 0) STAMP(22);
    #pragma unroll
    for (int i = 0; i < 4; i++)
      sm[i] = make_uint4(add_bf16x2(sm[i].x, p7[i].x), add_bf16x2(sm[i].y, p7[i].y), add_bf16x2(sm[i].z, p7[i].z), add_bf16x2(sm[i].w, p7[i].w));
    const uint32_t ost = abase + ((fs + 5) & 7) * 8192 + wq * 2048;
    uint32_t so = ost + (lane & 15) * 128 + (((lane >> 4) ^ (lane & 7)) << 4), lo = ost + (lane >> 3) * 128 + (((lane & 7) ^ (lane >> 3)) << 4);
    uint4* op = (uint4*)(out + (size_t)(mt * 128 + warp * 16 + (lane >> 3)) * DM + fs * 64) + (lane & 7);
    asm volatile("" : "+r"(so), "+r"(lo), "+l"(op));
    wg_wait<0>();
    keep<32>(accA);
    if (wq == 0) STAMP(wg * 24 + 12);
    #pragma unroll
    for (int i = 0; i < 4; i++) {
      const float* p = accA + 8 * i;
      stsm4(so ^ (i * 32),
            add_bf16x2(hr[4 * i], pack_bf16((p[0] + bf_lo(sm[i].x)) * r0, (p[1] + bf_hi(sm[i].x)) * r0)),
            add_bf16x2(hr[4 * i + 1], pack_bf16((p[2] + bf_lo(sm[i].y)) * r1, (p[3] + bf_hi(sm[i].y)) * r1)),
            add_bf16x2(hr[4 * i + 2], pack_bf16((p[4] + bf_lo(sm[i].z)) * r0, (p[5] + bf_hi(sm[i].z)) * r0)),
            add_bf16x2(hr[4 * i + 3], pack_bf16((p[6] + bf_lo(sm[i].w)) * r1, (p[7] + bf_hi(sm[i].w)) * r1)));
    }
    if (warp == 0) STAMP(23);
    __syncwarp();
    #pragma unroll
    for (int i = 0; i < 4; i++) {
      op[i * (4 * DM / 8)] = lds128((lo ^ ((i & 1) * 64)) + i * 512);
    }
#undef lane
    if (wq == 0) STAMP(wg * 24 + 13);
    if (warp == 0) GST32(96);
    PROF_DUMP();
    if (warp == 4) GSTAMP(PROF_SLOTS - 1);
  }
}

typedef CUresult (*EncFn)(CUtensorMap*, CUtensorMapDataType, cuuint32_t, void*, const cuuint64_t*, const cuuint64_t*, const cuuint32_t*,
                          const cuuint32_t*, CUtensorMapInterleave, CUtensorMapSwizzle, CUtensorMapL2promotion, CUtensorMapFloatOOBfill);
static void enc2d(EncFn enc, CUtensorMap* m, const void* p, uint64_t inner, uint64_t outer, uint32_t bi, uint32_t bo, bool swz = true) {
  cuuint64_t dims[2] = {inner, outer}; cuuint64_t str[1] = {inner * 2}; cuuint32_t box[2] = {bi, bo}; cuuint32_t es[2] = {1, 1};
  enc(m, CU_TENSOR_MAP_DATA_TYPE_BFLOAT16, 2, (void*)p, dims, str, box, es, CU_TENSOR_MAP_INTERLEAVE_NONE, swz ? CU_TENSOR_MAP_SWIZZLE_128B : CU_TENSOR_MAP_SWIZZLE_NONE,
      CU_TENSOR_MAP_L2_PROMOTION_L2_128B, CU_TENSOR_MAP_FLOAT_OOB_FILL_NONE);
}

extern "C" void kernel_launch(void* const* d_in, const int* in_sizes, int n_in, void* d_out, int out_size) {
  typedef const __nv_bfloat16* BP;
  BP x = (BP)d_in[0], Are = (BP)d_in[1], Aim = (BP)d_in[2], Bre = (BP)d_in[3], Bim = (BP)d_in[4], Cre = (BP)d_in[5], Cim = (BP)d_in[6],
     logdt = (BP)d_in[7], Dskip = (BP)d_in[8], Wg = (BP)d_in[10], Wu = (BP)d_in[11], Wd = (BP)d_in[12];
  void* fn = nullptr; cudaDriverEntryPointQueryResult qr;
  cudaGetDriverEntryPoint("cuTensorMapEncodeTiled", &fn, cudaEnableDefault, &qr);
  EncFn enc = (EncFn)fn;
  void* sp; cudaGetSymbolAddress(&sp, g_scr);
  Scratch* scr = (Scratch*)sp;
  void *hT = scr->hT, *U = scr->U, *X = scr->X;
  Maps maps;
  enc2d(enc, &maps.hT, hT, HP, DM, 64, 64);
  enc2d(enc, &maps.wg, Wg, FF, DM, 64, 32);
  enc2d(enc, &maps.wu, Wu, FF, DM, 64, 32);
  enc2d(enc, &maps.wd, Wd, DM, FF, 64, 32);
  enc2d(enc, &maps.out, d_out, DM, SEQ, 64, 16);
  enc2d(enc, &maps.E, U, 64, 2 * 144 * 128, 16, 128, false);
  enc2d(enc, &maps.U, U, 8192, 144, 64, 144);
  enc2d(enc, &maps.X, X, 8192, 144, 64, 144);
  Prm prm = {x, scr, logdt, Dskip, {Are, Aim, Bre, Bim, Cre, Cim}, Wg, Wu, Wd};
  cudaFuncSetAttribute(fused_kernel, cudaFuncAttributeMaxDynamicSharedMemorySize, SM_TOTAL);
  fused_kernel<<<128, 384, SM_TOTAL>>>(prm, (__nv_bfloat16*)d_out, maps);
}
```
